```python
import torch

def _softmax(x, axis=-1):
    return torch.softmax(x, dim=axis)

def _gelu(x):
    return torch.nn.functional.gelu(x, approximate='tanh')

def _silu(x):
    return torch.nn.functional.silu(x)

def _sigmoid(x):
    return torch.sigmoid(x)

def _layernorm(x, axis=-1, eps=1e-05):
    m = x.mean(dim=axis, keepdim=True)
    v = x.var(dim=axis, keepdim=True, unbiased=False)
    return (x - m) / torch.sqrt(v + eps)

def _scatter_add(tgt, idx, src, axis=0):
    return tgt.clone().index_add_(axis, idx, src)

def _segment_sum(src, seg, n):
    out = torch.zeros((n,) + src.shape[1:], dtype=src.dtype)
    return out.index_add_(0, seg, src)

def _pad(x, pw):
    flat = tuple((v for pair in reversed(pw) for v in pair))
    return torch.nn.functional.pad(x, flat)
kernel_name = 'adaLN_cond__sliding_block_cached__mixer_channel_mlp__decode'

def setup_inputs():

    _w = lambda a: (lambda t: t.to(torch.bfloat16) if t.is_floating_point() else t)(torch.as_tensor(a))

    def _A_setup():
        B, Sq, D = (1, 1, 576)
        Hq, Hkv, Sk, Dh = (32, 16, 32768, 128)
        assert Hq % Hkv == 0, (Hq, Hkv)
        return {'x': _w((lambda *s: torch.randn(*s, dtype=torch.bfloat16) * 0.1)(B, Sq, D)), 'k_cache': _w((lambda *s: torch.randn(*s, dtype=torch.bfloat16) * 0.8)(B, Hkv, Sk, Dh)), 'v_cache': _w((lambda *s: torch.randn(*s, dtype=torch.bfloat16) * 0.8)(B, Hkv, Sk, Dh)), 'wq': _w((lambda *s: torch.randn(*s, dtype=torch.bfloat16) * 0.8)(D, Hq * Dh) * D ** (-0.5)), 'wo': _w((lambda *s: torch.randn(*s, dtype=torch.bfloat16) * 0.8)(Hq * Dh, D) * (Hq * Dh) ** (-0.5))}
    _A_in = _A_setup()

    def _B_setup():
        B, S, D, F = (1, 1, 576, 4608)
        return {'x': _w((lambda *s: torch.randn(*s, dtype=torch.bfloat16) * 0.1)(B, S, D)), 'w1': _w((lambda *s: torch.randn(*s, dtype=torch.bfloat16) * 3.2)(D, F) * D ** (-0.5)), 'b1': _w((lambda *s: torch.randn(*s, dtype=torch.bfloat16) * 3.2)(F)), 'w2': _w((lambda *s: torch.randn(*s, dtype=torch.bfloat16) * 1.6)(F, D) * F ** (-0.5)), 'b2': _w((lambda *s: torch.randn(*s, dtype=torch.bfloat16) * 1.6)(D))}
    _B_in = _B_setup()
    return {'A_x': _A_in['x'], 'A_k_cache': _A_in['k_cache'], 'A_v_cache': _A_in['v_cache'], 'A_wq': _A_in['wq'], 'A_wo': _A_in['wo'], 'B_x': _B_in['x'], 'B_w1': _B_in['w1'], 'B_b1': _B_in['b1'], 'B_w2': _B_in['w2'], 'B_b2': _B_in['b2'], 'c': _w((lambda *s: torch.randn(*s, dtype=torch.bfloat16) * 0.4)(1, 576) * 8.0), 'w_mod': _w((lambda *s: torch.randn(*s, dtype=torch.bfloat16) * 0.4)(576, 6 * 576) * 576 ** (-0.5) * 8.0)}

def reference(A_x, A_k_cache, A_v_cache, A_wq, A_wo, B_x, B_w1, B_b1, B_w2, B_b2, c, w_mod):

    def _A_ref(x, k_cache, v_cache, wq, wo):
        B, Sq, D = x.shape
        Hq, Dh = (32, 128)
        Hkv, Sk = (k_cache.shape[1], k_cache.shape[2])
        W = min(4096, max(256, Sk // 4))
        rep = Hq // Hkv
        q = (lambda x, *d: x.permute(*d))((x @ wq).reshape(B, Sq, Hq, Dh), 0, 2, 1, 3)
        k = (lambda x, n, axis: torch.repeat_interleave(x, n, dim=axis))(k_cache[:, :, Sk - W:, :], rep, axis=1)
        v = (lambda x, n, axis: torch.repeat_interleave(x, n, dim=axis))(v_cache[:, :, Sk - W:, :], rep, axis=1)
        scores = torch.einsum('bhqd,bhkd->bhqk', q, k) * Dh ** (-0.5)
        p = _softmax(scores, axis=-1)
        o = torch.einsum('bhqk,bhkd->bhqd', p, v)
        return (lambda x, *d: x.permute(*d))(o, 0, 2, 1, 3).reshape(B, Sq, Hq * Dh) @ wo

    def _B_ref(x, w1, b1, w2, b2):
        y = _layernorm(x, axis=-1)
        h = _gelu(torch.einsum('bsd,df->bsf', y, w1) + b1)
        return torch.einsum('bsf,fd->bsd', h, w2) + b2
    x = A_x
    mod = (_silu(c) @ w_mod).reshape(c.shape[0], 6, 1, -1)
    sa, ca, ga, sb, cb, gb = (mod[:, 0].clone(), mod[:, 1].clone(), mod[:, 2].clone(), mod[:, 3].clone(), mod[:, 4].clone(), mod[:, 5].clone())
    h = _layernorm(x, axis=-1) * (1 + ca) + sa
    x = x + ga * _A_ref(h, A_k_cache, A_v_cache, A_wq, A_wo)
    h = _layernorm(x, axis=-1) * (1 + cb) + sb
    x = x + gb * _B_ref(h, B_w1, B_b1, B_w2, B_b2)
    return x
```

```cpp
#include <cuda_runtime.h>
#include <cuda_bf16.h>
#include <cuda.h>
#include <stdint.h>

namespace {

constexpr int D = 576, HKV = 16, SK = 32768, WIN = 4096, FF = 4608;
constexpr int NATT = 128;
constexpr int NCTA = 132;
constexpr int NCW = 12;
constexpr int NCT = NCW * 32;
constexpr int NTHREADS = NCT + 128;

constexpr int SM_K = 0;
constexpr int SM_WO = 0;
constexpr int SM_W2 = 36864;
constexpr int SM_W1 = 82944;
constexpr int SM_W1X = 119808;
constexpr int SM_RING = 131072;
constexpr int SM_M = SM_RING;
constexpr int SM_WQ = SM_RING + 27648;
constexpr int SM_MISC = SM_RING + 5 * 16384;
constexpr int SM_MOD = SM_MISC;
constexpr int SM_VEC = SM_MOD + 6912;
constexpr int SM_XN = SM_VEC + 1152;
constexpr int SM_Q = SM_XN + 1152;
constexpr int SM_S = SM_Q + 512;
constexpr int SM_P = SM_S + 4096;
constexpr int SM_RED = SM_P + 2048;
constexpr int SM_SMALL = SM_RED + 1920;
constexpr int SM_O = SM_SMALL + 256;
constexpr int SM_BAR = SM_O + 128;
constexpr int SM_TOTAL = SM_BAR + 40 * 8;
static_assert(SM_TOTAL <= 232448, "smem");

enum { IT_M = 0, IT_WQ = 1, IT_K = 4, IT_V = 12, IT_WO = 20, IT_W2 = 22, IT_W1 = 24, IT_W2C = 27, IT_W1X = 28, NITEM = 31,
       BF_WQ = 31, BF_K = 32, BF_V0 = 33  , NBAR_USED = 36 };
#define TAILSEQ 0xc0d1e234589a67bull
#define NWIN_A 4
#define NWIN_B 5
#define NWIN_C 4
#define WIN_AB (IT_K + 4)
#define WIN_BC 24
#define POLL_SLEEP 0
#define POLL_SLEEP2 0
#define EVICT_MODE 2
#define BAR3N 160
#define PACE_RATE 24.0f
#define PACE_STAG(c) (c)
#define PACE_W1 90
#define PACE_W2 90
#define PROBE_REPS 3
#define MOD_BACKOFF 150
#define W1_PROMO 2
#define EXPW1 0
#define PACE_T0 400
#define PACE_LEAD 12000
#define PFHINT ".L2::128B"

enum { BX_X2 = 0,
       BX_PROBE = 128,
       BX_PART = 512,
       BX_O = BX_PART + NATT * 512,
       BX_MOD = BX_O + NATT * 512,
       BX_Q = BX_MOD + 576,
       BX_ML = BX_Q + NATT * 8,
       BX_SIDE = BX_ML + NATT * 2,
       BX_EPOCH = BX_SIDE + 64,
       BX_TOTAL = BX_EPOCH + 8 };
__device__ uint4 g_box[BX_TOTAL + 512];

#define TS(i) do {} while (0)

constexpr unsigned SPIN_MAX = 1u << 22;
#define PIN(x) asm volatile("" : "+r"(x))
#define PIN64(x) asm volatile("" : "+l"(x))
#define PINF(x) asm volatile("" : "+f"(x))

__device__ __forceinline__ uint32_t smem_u32(const void* p) { return (uint32_t)__cvta_generic_to_shared(p); }
__device__ __forceinline__ void mbar_init(uint32_t bar, uint32_t cnt) {
    asm volatile("mbarrier.init.shared::cta.b64 [%0], %1;" ::"r"(bar), "r"(cnt) : "memory");
}
__device__ __forceinline__ void mbar_expect_tx(uint32_t bar, uint32_t bytes) {
    asm volatile("mbarrier.arrive.expect_tx.shared::cta.b64 _, [%0], %1;" ::"r"(bar), "r"(bytes) : "memory");
}
__device__ __forceinline__ void mbar_arrive(uint32_t bar) {
    asm volatile("mbarrier.arrive.shared::cta.b64 _, [%0];" ::"r"(bar) : "memory");
}
__device__ __forceinline__ void mbar_wait(uint32_t bar) {
    uint32_t ok;
    unsigned n = 0;
#pragma unroll 1
    do {
        asm volatile("{\n.reg .pred p;\nmbarrier.try_wait.parity.shared::cta.b64 p, [%1], 0;\nselp.u32 %0, 1, 0, p;\n}"
                     : "=r"(ok) : "r"(bar) : "memory");
    } while (!ok && ++n < SPIN_MAX);
}
__device__ __forceinline__ bool mbar_test(uint32_t bar) {
    uint32_t ok;
    asm volatile("{\n.reg .pred p;\nmbarrier.test_wait.parity.shared::cta.b64 p, [%1], 0;\nselp.u32 %0, 1, 0, p;\n}"
                 : "=r"(ok) : "r"(bar) : "memory");
    return __all_sync(0xffffffffu, ok);
}
__device__ __forceinline__ void tma2d(uint32_t dst, const CUtensorMap* map, int c0, int c1, uint32_t bar, uint64_t pol) {
    asm volatile("cp.async.bulk.tensor.2d.shared::cluster.global.mbarrier::complete_tx::bytes.L2::cache_hint [%0], [%1, {%3, %4}], [%2], %5;"
                 ::"r"(dst), "l"(map), "r"(bar), "r"(c0), "r"(c1), "l"(pol) : "memory");
}
__device__ __forceinline__ void cp16(uint32_t dst, const void* src) {
    asm volatile("cp.async.cg.shared.global" PFHINT " [%0], [%1], 16;" ::"r"(dst), "l"(src) : "memory");
}
__device__ __forceinline__ void cp_arrive(uint32_t bar) {
    asm volatile("cp.async.mbarrier.arrive.noinc.shared::cta.b64 [%0];" ::"r"(bar) : "memory");
}
__device__ __forceinline__ void cbar() { asm volatile("bar.sync 1, %0;" ::"n"(NCT) : "memory"); }

__device__ __forceinline__ uint32_t lds32(uint32_t a) { uint32_t v; asm volatile("ld.shared.u32 %0, [%1];" : "=r"(v) : "r"(a) : "memory"); return v; }
__device__ __forceinline__ uint32_t lds16(uint32_t a) { uint32_t v; asm volatile("ld.shared.u16 %0, [%1];" : "=r"(v) : "r"(a) : "memory"); return v; }
__device__ __forceinline__ float ldsf(uint32_t a) { float v; asm volatile("ld.shared.f32 %0, [%1];" : "=f"(v) : "r"(a) : "memory"); return v; }
__device__ __forceinline__ float4 ldsf4(uint32_t a) {
    float4 v;
    asm volatile("ld.shared.v4.f32 {%0,%1,%2,%3}, [%4];" : "=f"(v.x), "=f"(v.y), "=f"(v.z), "=f"(v.w) : "r"(a) : "memory");
    return v;
}
__device__ __forceinline__ void sts32(uint32_t a, uint32_t v) { asm volatile("st.shared.u32 [%0], %1;" ::"r"(a), "r"(v) : "memory"); }
__device__ __forceinline__ void sts16(uint32_t a, uint32_t v) { asm volatile("st.shared.u16 [%0], %1;" ::"r"(a), "r"(v) : "memory"); }
__device__ __forceinline__ void stsf(uint32_t a, float v) { asm volatile("st.shared.f32 [%0], %1;" ::"r"(a), "f"(v) : "memory"); }
__device__ __forceinline__ void sts64(uint32_t a, uint32_t x, uint32_t y) { asm volatile("st.shared.v2.u32 [%0], {%1,%2};" ::"r"(a), "r"(x), "r"(y) : "memory"); }

__device__ __forceinline__ void st_msg(uint4* p, uint32_t a, uint32_t b, uint32_t c, uint32_t d) {
    asm volatile("{\n.reg .b128 t;\n.reg .b64 lo, hi;\nmov.b64 lo, {%1, %2};\nmov.b64 hi, {%3, %4};\nmov.b128 t, {lo, hi};\n"
                 "st.relaxed.gpu.global.b128 [%0], t;\n}" ::"l"(p), "r"(a), "r"(b), "r"(c), "r"(d) : "memory");
}
__device__ __forceinline__ uint4 ld_msg(const uint4* p) {
    uint4 v;
    asm volatile("{\n.reg .b128 t;\n.reg .b64 lo, hi;\nld.relaxed.gpu.global.b128 t, [%4];\nmov.b128 {lo, hi}, t;\n"
                 "mov.b64 {%0, %1}, lo;\nmov.b64 {%2, %3}, hi;\n}" : "=r"(v.x), "=r"(v.y), "=r"(v.z), "=r"(v.w) : "l"(p) : "memory");
    return v;
}
template <int BACKOFF = 0>
__device__ __forceinline__ uint4 poll_msg(const uint4* p, uint32_t tag) {
    uint4 v;
    v.w = tag + 1;
    unsigned n = 0;
#pragma unroll 1
    do {
        if (BACKOFF && n) __nanosleep(BACKOFF);
        if (v.w != tag) v = ld_msg(p);
    } while (__any_sync(0xffffffffu, v.w != tag) && ++n < SPIN_MAX);
    return v;
}
__device__ __forceinline__ uint32_t ld_acq32(const uint32_t* p) {
    uint32_t v;
    asm volatile("ld.acquire.gpu.global.u32 %0, [%1];" : "=r"(v) : "l"(p) : "memory");
    return v;
}
__device__ __forceinline__ uint32_t near_half(uint4* p, uint32_t step, int dbg) {
    uint32_t best[2] = {0xffffffffu, 0xffffffffu};
#pragma unroll 1
    for (int r = 0; r < PROBE_REPS * 2; r++) {
        uint32_t c0, c1 = 0;
        asm volatile("{\n.reg .pred p;\n.reg .u32 v;\nmov.u32 %0, %clock;\natom.relaxed.gpu.global.exch.b32 v, [%2], 0;\n"
                     "setp.ne.u32 p, v, 1;\n@p mov.u32 %1, %clock;\n}" : "=r"(c0), "+r"(c1) : "l"(p + (r & 1) * 256 + (r >> 1) * step) : "memory");
        if (r & 1) best[1] = min(best[1], c1 - c0); else best[0] = min(best[0], c1 - c0);
    }
    return best[1] < best[0];
}
__device__ __forceinline__ void st_msg8(uint2* p, uint32_t a, uint32_t b) {
    asm volatile("{\n.reg .b64 t;\nmov.b64 t, {%1, %2};\nst.relaxed.gpu.global.b64 [%0], t;\n}" ::"l"(p), "r"(a), "r"(b) : "memory");
}
__device__ __forceinline__ uint2 ld_msg8(const uint2* p) {
    uint2 v;
    asm volatile("{\n.reg .b64 t;\nld.relaxed.gpu.global.b64 t, [%2];\nmov.b64 {%0, %1}, t;\n}" : "=r"(v.x), "=r"(v.y) : "l"(p) : "memory");
    return v;
}
__device__ __forceinline__ uint32_t ldg16(const __nv_bfloat16* p) {
    uint32_t v;
    asm volatile("ld.global.nc.u16 %0, [%1];" : "=r"(v) : "l"(p));
    return v;
}

__device__ __forceinline__ void ldsm4(uint32_t a, uint32_t* r) {
    asm volatile("ldmatrix.sync.aligned.m8n8.x4.shared.b16 {%0,%1,%2,%3}, [%4];" : "=r"(r[0]), "=r"(r[1]), "=r"(r[2]), "=r"(r[3]) : "r"(a) : "memory");
}
__device__ __forceinline__ void ldsm4t(uint32_t a, uint32_t* r) {
    asm volatile("ldmatrix.sync.aligned.m8n8.x4.trans.shared.b16 {%0,%1,%2,%3}, [%4];" : "=r"(r[0]), "=r"(r[1]), "=r"(r[2]), "=r"(r[3]) : "r"(a) : "memory");
}
__device__ __forceinline__ void ldsm2t(uint32_t a, uint32_t* r) {
    asm volatile("ldmatrix.sync.aligned.m8n8.x2.trans.shared.b16 {%0,%1}, [%2];" : "=r"(r[0]), "=r"(r[1]) : "r"(a) : "memory");
}
__device__ __forceinline__ void mma16(float* c, uint32_t a0, uint32_t a1, uint32_t a2, uint32_t a3, uint32_t b0, uint32_t b1) {
    asm volatile("mma.sync.aligned.m16n8k16.row.col.f32.bf16.bf16.f32 {%0,%1,%2,%3}, {%4,%5,%6,%7}, {%8,%9}, {%0,%1,%2,%3};"
                 : "+f"(c[0]), "+f"(c[1]), "+f"(c[2]), "+f"(c[3]) : "r"(a0), "r"(a1), "r"(a2), "r"(a3), "r"(b0), "r"(b1));
}
__device__ __forceinline__ void mma8(float* c, uint32_t a0, uint32_t a1, uint32_t b0) {
    asm volatile("mma.sync.aligned.m16n8k8.row.col.f32.bf16.bf16.f32 {%0,%1,%2,%3}, {%4,%5}, {%6}, {%0,%1,%2,%3};"
                 : "+f"(c[0]), "+f"(c[1]), "+f"(c[2]), "+f"(c[3]) : "r"(a0), "r"(a1), "r"(b0));
}

__device__ __forceinline__ uint32_t pack2(float lo, float hi) {
    uint32_t r;
    asm("cvt.rn.bf16x2.f32 %0, %1, %2;" : "=r"(r) : "f"(hi), "f"(lo));
    return r;
}
__device__ __forceinline__ float rb(float x) { return __uint_as_float(pack2(0.f, x)); }
__device__ __forceinline__ uint32_t f2b(float x) { return pack2(x, 0.f); }
__device__ __forceinline__ float blo(uint32_t u) { return __uint_as_float(u << 16); }
__device__ __forceinline__ float bhi(uint32_t u) { return __uint_as_float(u & 0xffff0000u); }
__device__ __forceinline__ float ex2(float x) { float r; asm("ex2.approx.ftz.f32 %0, %1;" : "=f"(r) : "f"(x)); return r; }
__device__ __forceinline__ float rcp(float x) { float r; asm("rcp.approx.ftz.f32 %0, %1;" : "=f"(r) : "f"(x)); return r; }
constexpr float LOG2E = 1.4426950408889634f;
__device__ __forceinline__ float sigm(float x) { return rcp(1.f + ex2(-LOG2E * x)); }

__device__ __forceinline__ float3 layernorm3(float3 v, uint32_t scr, uint32_t scr_w, int lane) {
    float s = v.x + v.y + v.z, q = v.x * v.x + v.y * v.y + v.z * v.z;
#pragma unroll
    for (int o = 16; o > 0; o >>= 1) {
        s += __shfl_xor_sync(0xffffffffu, s, o);
        q += __shfl_xor_sync(0xffffffffu, q, o);
    }
    if (lane == 0) sts64(scr_w, __float_as_uint(s), __float_as_uint(q));
    asm volatile("bar.sync 4, 192;" ::: "memory");
    const float4 e0 = ldsf4(scr), e1 = ldsf4(scr + 16), e2 = ldsf4(scr + 32);
    const float mean = ((e0.x + e0.z) + (e1.x + e1.z) + (e2.x + e2.z)) * (1.0f / D);
    const float var = ((e0.y + e0.w) + (e1.y + e1.w) + (e2.y + e2.w)) * (1.0f / D) - mean * mean;
    const float mb = rb(mean);
    float den;
    asm("sqrt.approx.ftz.f32 %0, %1;" : "=f"(den) : "f"(rb(rb(fmaxf(var, 0.f)) + 1e-5f)));
    const float inv = rcp(rb(den));
    return make_float3(rb(rb(v.x - mb) * inv), rb(rb(v.y - mb) * inv), rb(rb(v.z - mb) * inv));
}

template <int NT>
__device__ __forceinline__ void strip_load(uint32_t p4, uint32_t p2, int x, uint32_t (&b)[NT][6]) {
#pragma unroll
    for (int n = 0; n < NT; n++) {
        ldsm4t(p4 + ((n ^ x) << 4), &b[n][0]);
        ldsm2t(p2 + ((n ^ x) << 4), &b[n][4]);
    }
}
__device__ __forceinline__ float red_sum(uint32_t red_r) {
    cbar();
    float v[NCW];
#pragma unroll
    for (int w = 0; w < NCW; w++) v[w] = ldsf(red_r + w * 160);
    return ((v[0] + v[1]) + (v[2] + v[3])) + ((v[4] + v[5]) + (v[6] + v[7])) + ((v[8] + v[9]) + (v[10] + v[11]));
}
template <int NT>
__device__ __forceinline__ void strip_mma_store(const uint32_t (&a)[6], const uint32_t (&b)[NT][6], uint32_t red_w, int lane) {
    float c[NT][4];
#pragma unroll
    for (int n = 0; n < NT; n++) c[n][0] = c[n][1] = c[n][2] = c[n][3] = 0.f;
#pragma unroll
    for (int k = 0; k < 3; k++)
#pragma unroll
        for (int n = 0; n < NT; n++) mma16(c[n], a[2 * k], a[2 * k], a[2 * k + 1], a[2 * k + 1], b[n][2 * k], b[n][2 * k + 1]);
    if (lane < 4) {
#pragma unroll
        for (int n = 0; n < NT; n++) sts64(red_w + n * 32, __float_as_uint(c[n][0]), __float_as_uint(c[n][1]));
    }
}
template <int NT>
__device__ __forceinline__ float strip_mma(const uint32_t (&a)[6], const uint32_t (&b)[NT][6], uint32_t red_w, uint32_t red_r, int lane) {
    strip_mma_store<NT>(a, b, red_w, lane);
    return red_sum(red_r);
}

#define TSARG
#define TSPASS(i)
__device__ __forceinline__ float reduce_part(const uint4* p, uint32_t tag, int lane TSARG) {
    uint4 v[8];
    bool pend;
    unsigned n = 0;
#pragma unroll
    for (int i = 0; i < 8; i++) v[i].w = tag + 1;
#pragma unroll 1
    do {
#pragma unroll
        for (int i = 0; i < 8; i++) if (v[i].w != tag) v[i] = ld_msg(p + i * 32);
        pend = false;
#pragma unroll
        for (int i = 0; i < 8; i++) pend |= v[i].w != tag;
    } while (__any_sync(0xffffffffu, pend) && ++n < SPIN_MAX);
#define F(i, c) __uint_as_float(v[i].c)
    float s0 = ((F(0, x) + F(1, x)) + (F(2, x) + F(3, x))) + ((F(4, x) + F(5, x)) + (F(6, x) + F(7, x)));
    float s1 = ((F(0, y) + F(1, y)) + (F(2, y) + F(3, y))) + ((F(4, y) + F(5, y)) + (F(6, y) + F(7, y)));
    float s2 = ((F(0, z) + F(1, z)) + (F(2, z) + F(3, z))) + ((F(4, z) + F(5, z)) + (F(6, z) + F(7, z)));
#undef F
#pragma unroll
    for (int o = 16; o > 1; o >>= 1) {
        s0 += __shfl_xor_sync(0xffffffffu, s0, o);
        s1 += __shfl_xor_sync(0xffffffffu, s1, o);
        s2 += __shfl_xor_sync(0xffffffffu, s2, o);
    }
    return lane < 2 ? s0 : lane < 4 ? s1 : s2;
}

struct Params {
    const __nv_bfloat16 *wmod, *c, *x, *b1, *b2;
    __nv_bfloat16* out;
    uint4* box;
    alignas(64) CUtensorMap m_wq, m_k, m_v, m_wo, m_w1, m_w2, m_w2b, m_w1x;
};

__global__ void __launch_bounds__(NTHREADS, 1) fused_kernel(const __grid_constant__ Params P) {
    extern __shared__ __align__(1024) unsigned char smem[];
    uint32_t sb = smem_u32(smem);
    PIN(sb);
    uint32_t tid = threadIdx.x, warp = tid >> 5, lane = tid & 31;
    uint32_t cta = blockIdx.x;
#define BAR(i) (sb + SM_BAR + (i) * 8)
    uint32_t grp = cta >> 3, rk = cta & 7;

    if (warp == NCW) {
        uint32_t t_start;
        asm volatile("mov.u32 %0, %globaltimer_lo;" : "=r"(t_start));
        if (lane < 8) asm volatile("prefetch.tensormap [%0];" ::"l"(&P.m_wq + lane) : "memory");
        if (lane == 0) {
            TS(0);
#pragma unroll
            for (int i = 0; i < NBAR_USED; i++)
                mbar_init(BAR(i), i == IT_M ? NCT : i >= BF_V0 ? 4 : 1);
            asm volatile("fence.proxy.async.shared::cta;" ::: "memory");
        }
        __syncwarp();
        asm volatile("bar.arrive 2, %0;" ::"n"(NTHREADS) : "memory");
        if (cta >= NATT) return;
        int mapi = 1, c0 = 0, c1, bytes = 16384, fbar = -1;
        uint32_t dst;
        const int i = lane < 16 ? lane : 16 + (int)((TAILSEQ >> (4 * ((30 - lane) & 15))) & 15);
        if (i < IT_K) {
            mapi = 0; c0 = cta * 32; c1 = (i - IT_WQ) * 192; dst = SM_WQ + (i - IT_WQ) * 12288; bytes = 12288;
        } else if (i < IT_WO) {
            const int k = (i - IT_K) & 7;
            c1 = (grp * SK + (SK - WIN) + (k * 8 + rk) * 64) * 2;
            dst = SM_K + k * 16384;
            if (i >= IT_V) {
                mapi = 2; dst = SM_RING + (k == 0 || k == 5 ? 4 : k < 5 ? k - 1 : k - 6) * 16384;
                fbar = k == 1 ? BF_WQ : k >= 5 ? BF_V0 + k - 5 : -1;
            }
        } else if (i < IT_W2) {
            mapi = 3; c1 = (grp * 256 + (i - IT_WO) * 128 + rk * 16) * 9; dst = SM_WO + (i - IT_WO) * 18432; bytes = 18432;
        } else if (i < IT_W1) {
            mapi = 5; c1 = (cta * 32 + (i - IT_W2) * 16) * 9; dst = SM_W2 + (i - IT_W2) * 18432; bytes = 18432;
        } else if (i < IT_W2C) {
            mapi = 4; c0 = cta * 32; c1 = (i - IT_W1) * 192; dst = SM_W1 + (i - IT_W1) * 12288; bytes = 12288;
        } else if (i == IT_W2C) {
            mapi = 6; c1 = (4096 + (cta >> 1) * 8) * 9; dst = SM_W2 + 2 * 18432; bytes = 9216;
        } else {
            mapi = 7; c0 = 4096 + (cta >> 1) * 8; c1 = (i - IT_W1X) * 192; dst = SM_W1X + (i - IT_W1X) * 3072; bytes = 3072;
        }
        if (i >= IT_WO) fbar = BF_K;
        uint64_t pol;
        if (EVICT_MODE == 2 || (EVICT_MODE == 1 && i >= IT_K && i < IT_WO) || (EVICT_MODE == 3 && mapi != 4) || (EVICT_MODE == 4 && i < IT_W2)) asm volatile("createpolicy.fractional.L2::evict_first.b64 %0, 1.0;" : "=l"(pol));
        else asm volatile("createpolicy.fractional.L2::evict_normal.b64 %0, 1.0;" : "=l"(pol));
        int cum = i < IT_WQ ? 27648 : i >= IT_W2C ? bytes / 2 : bytes;
#pragma unroll
        for (int o = 1; o < 32; o <<= 1) { const int u = __shfl_up_sync(0xffffffffu, cum, o); if (lane >= o) cum += u; }
        const uint32_t t_iss = t_start + PACE_T0 + (uint32_t)(max(cum - PACE_LEAD - (int)(PACE_STAG(cta) * 128), 0) * (1.0f / PACE_RATE));
#pragma unroll 1
        for (int k = IT_WQ; k < NITEM; k++) {
            const int fk = __shfl_sync(0xffffffffu, fbar, k);
            const int gate = k - (k < WIN_AB ? NWIN_A : k < WIN_BC ? NWIN_B : NWIN_C);
            const int gi = __shfl_sync(0xffffffffu, i, gate & 31);
            if (gate >= 0) mbar_wait(BAR(gi));
            if (fk >= 0) mbar_wait(BAR(fk));
            {
                const uint32_t tk = __shfl_sync(0xffffffffu, t_iss, k);
                uint32_t now;
                unsigned n = 0;
                do { asm volatile("mov.u32 %0, %globaltimer_lo;" : "=r"(now)); } while ((int)(now - tk) < 0 && ++n < SPIN_MAX);
            }
            if (lane == k) {
                const uint32_t bk = BAR(i);
                mbar_expect_tx(bk, bytes);
                tma2d(sb + dst, &P.m_wq + mapi, c0, c1, bk, pol);
                TS(32 + k);
            }
            __syncwarp();
        }
        return;
    }

    if (warp > NCW) {
        asm volatile("bar.sync 2, %0;" ::"n"(NTHREADS) : "memory");
        if (cta >= NATT) return;
        const uint32_t k = warp - NCW - 1;
        uint4* const box = P.box;
        uint4* const pair = box + (k == 0 ? BX_PART + cta * 512 : k == 1 ? BX_O + cta * 512 : BX_PROBE + (cta & 15) * 2);
        uint32_t epoch, h = 0;
        asm volatile("ld.relaxed.gpu.global.u32 %0, [%1];" : "=r"(epoch) : "l"(box + BX_EPOCH) : "memory");
        const uint32_t step = k == 2 ? 40 : 72;
        if (lane < 4 * PROBE_REPS) st_msg(pair + ((lane >> 1) & 1) * 256 + (lane >> 2) * step + (lane & 1), 0u, 0u, 0u, 0u);
        mbar_wait(BAR(IT_M));
        if (lane == 0) {
            h = near_half(pair, step, k);
            sts32(sb + SM_O + 100 + k * 4, h);
            if (k == 0) TS(25);
        }
        h = __shfl_sync(0xffffffffu, h, 0);
        asm volatile("bar.arrive 7, %0;" ::"n"(NCT + 96) : "memory");
        if (k == 2) return;
#pragma unroll 1
        for (uint32_t i = 0; i < 8u >> k; i++) st_msg(pair + h * 256 + i * 32 + lane, 0u, 0u, 0u, 0u);
        __syncwarp();
        if (lane == 0)
            asm volatile("st.release.gpu.global.u32 [%0], %1;" ::"l"(reinterpret_cast<uint32_t*>(box + BX_SIDE) + cta * 2 + k),
                         "r"(((epoch * 2 + 1) << 1) | h) : "memory");
        if (lane == 0 && k == 0) TS(26);
        return;
    }

    bool spare = cta >= NATT;
    uint32_t strip0 = spare ? cta * 4 - 3 * NATT : cta;
    uint32_t m_base = spare ? sb : sb + SM_M;
    {
        const uint32_t row = (lane * 11) >> 5;
        const char* src = reinterpret_cast<const char*>(P.wmod) + ((warp * 48 + row) * (6 * D * 2) + strip0 * 48 + (lane - row * 3) * 16);
        uint32_t d = m_base + warp * 2304 + lane * 16;
#pragma unroll 1
        for (int s = spare ? 4 : 1; s > 0; s--) {
            if (lane < 30) {
#pragma unroll
                for (int k = 0; k < 4; k++) cp16(d + k * 480, src + k * 10 * (6 * D * 2));
                if (lane < 24) cp16(d + 4 * 480, src + 4 * 10 * (6 * D * 2));
            }
            src += 48; d += 27648;
        }
    }
    tid = __shfl_sync(0xffffffffu, tid, lane); cta = __shfl_sync(0xffffffffu, cta, 0);
    warp = tid >> 5; lane = tid & 31; grp = cta >> 3; rk = cta & 7;
    spare = cta >= NATT; strip0 = spare ? cta * 4 - 3 * NATT : cta; m_base = spare ? sb : sb + SM_M;
    const uint32_t t = lane & 3, gq = lane >> 2;
    uint4* const box = P.box;
    const uint32_t li = tid - 64;
    const bool is_ln = li < 192;
    const bool is_red = cta < 96 && warp == 8;
    const uint32_t lcol = is_ln ? 48 * (li >> 4) + 8 * (li & 1) + ((li >> 1) & 7) : min(48 * grp + 8 * min(lane, 5u) + rk, D - 33u + 32u);
    const uint32_t vi = warp * 24 + min(lane, 23u);
    uint32_t cv, epoch, x0, x1, x2;
    asm volatile("ld.global.nc.u32 %0, [%1];" : "=r"(cv) : "l"(reinterpret_cast<const uint32_t*>(P.c) + vi));
    asm volatile("ld.relaxed.gpu.global.u32 %0, [%1];" : "=r"(epoch) : "l"(box + BX_EPOCH) : "memory");
    x0 = ldg16(P.x + lcol);
    x1 = ldg16(is_ln ? P.x + lcol + 16 : P.b1 + min(tid < 32 ? cta * 32 + tid : 4064 + (cta >> 1) * 8 + tid, FF - 1u));
    x2 = ldg16(is_ln ? P.x + lcol + 32 : P.b2 + lcol);
    asm volatile("cp.async.commit_group;" ::: "memory");
    asm volatile("bar.sync 2, %0;" ::"n"(NTHREADS) : "memory");
    cp_arrive(BAR(IT_M));
    if (warp == 8) {
        const uint32_t idx = lane < 16 ? BX_MOD + strip0 * 4 + lane : lane < 24 ? BX_Q + cta * 8 + lane - 16 : BX_ML + cta * 2 + lane - 24;
        if (spare ? lane < 16 : (lane < 4 || (lane >= 16 && lane < 26))) st_msg(box + idx, 0u, 0u, 0u, 0u);
        if (cta < 96 && lane >= 28) st_msg8(reinterpret_cast<uint2*>(box + BX_X2 + (lane & 2) * 128) + cta * 2 + (lane & 1), 0u, 0u);
    }
    if (tid == 0) TS(20);
    uint32_t a[6];
    {
        PIN(cv);
        const float c0 = blo(cv), c1 = bhi(cv);
        const uint32_t av = pack2(c0 * sigm(c0), c1 * sigm(c1));
#pragma unroll
        for (int i = 0; i < 6; i++) a[i] = __shfl_sync(0xffffffffu, av, i * 4 + t);
    }
    const uint32_t scr_w = sb + SM_SMALL + (warp - 2) * 8;
    PIN(x0); PIN(x1); PIN(x2);
    if (is_ln) {
        const float3 xv = layernorm3(make_float3(blo(x0), blo(x1), blo(x2)), sb + SM_SMALL + 192, scr_w + 192, lane);
        sts16(sb + SM_XN + lcol * 2, __float_as_uint(xv.x) >> 16);
        sts16(sb + SM_XN + lcol * 2 + 32, __float_as_uint(xv.y) >> 16);
        sts16(sb + SM_XN + lcol * 2 + 64, __float_as_uint(xv.z) >> 16);
    }
    const uint32_t tag = epoch * 2 + 1, tag2 = epoch * 2 + 2;
    const uint32_t red_w = sb + SM_RED + warp * 160 + lane * 8, red_r = sb + SM_RED + min(tid, 39u) * 4;
    const uint32_t r4 = warp * 48 + lane, r2 = warp * 48 + 32 + (lane & 15);
    if (tid == 0) TS(1);

    asm volatile("cp.async.wait_group 0;" ::: "memory");
    __syncwarp();
    if (tid == 0) TS(19);
#pragma unroll 1
    for (uint32_t s = 0; s < (spare ? 4u : 1u); s++) {
        uint32_t b[3][6];
        strip_load<3>(m_base + s * 27648 + r4 * 48, m_base + s * 27648 + r2 * 48, 0, b);
        const float r = strip_mma<3>(a, b, red_w, red_r, lane);
        if (warp == 0) {
            sts16(sb + SM_O + lane * 2, f2b(r));
            __syncwarp();
            if (lane < 4) st_msg(box + BX_MOD + (strip0 + s) * 4 + lane, lds32(sb + SM_O + lane * 12), lds32(sb + SM_O + lane * 12 + 4),
                                 lds32(sb + SM_O + lane * 12 + 8), tag);
        }
        cbar();
    }
    if (spare) return;
    if (tid == 0) TS(2);

    {
        const uint32_t sl = ((lane >> 3) & 1) * 96 + warp * 8 + (lane & 7);
        const uint4 v = poll_msg<MOD_BACKOFF>(box + BX_MOD + sl, tag);
        const uint32_t d = sb + SM_MOD + sl * 12;
        sts32(d, v.x); sts32(d + 4, v.y); sts32(d + 8, v.z);
    }
    __syncwarp();
    {
        const uint32_t xn = lds32(sb + SM_XN + vi * 4), sa = lds32(sb + SM_MOD + vi * 4), ca = lds32(sb + SM_MOD + 1152 + vi * 4);
        const uint32_t one = pack2(1.f + blo(ca), 1.f + bhi(ca));
        const uint32_t pr = pack2(blo(xn) * blo(one), bhi(xn) * bhi(one));
        const uint32_t av = pack2(blo(pr) + blo(sa), bhi(pr) + bhi(sa));
#pragma unroll
        for (int i = 0; i < 6; i++) a[i] = __shfl_sync(0xffffffffu, av, i * 4 + t);
    }
    if (tid == 0) TS(3);
    mbar_wait(BAR(IT_WQ + (warp >> 2)));
    {
        uint32_t b[4][6];
        strip_load<4>(sb + SM_WQ + r4 * 64, sb + SM_WQ + r2 * 64, (lane >> 1) & 3, b);
        const float r = strip_mma<4>(a, b, red_w, red_r, lane);
        if (warp == 0) {
            sts16(sb + SM_O + lane * 2, f2b(r));
            __syncwarp();
            if (lane < 8) st_msg(box + BX_Q + cta * 8 + lane, lds32(sb + SM_O + lane * 8), lds32(sb + SM_O + lane * 8 + 4), 0u, tag);
            if (lane == 0) { mbar_arrive(BAR(BF_WQ)); TS(4); }
        }
    }
    if (li < 64) {
        const uint4 v = poll_msg(box + BX_Q + grp * 64 + li, tag);
        sts64(sb + SM_Q + li * 8, v.x, v.y);
    }
    asm volatile("bar.sync 7, %0;" ::"n"(NCT + 96) : "memory");
    if (tid == 0) TS(5);
    const uint32_t h_own = lds32(sb + SM_O + 100) | (lds32(sb + SM_O + 104) << 1) | (lds32(sb + SM_O + 108) << 2);
    const uint32_t ob = sb + SM_O + t * 4;

    if (warp < 8) {
        uint32_t bq[4][2];
        const uint32_t msk = gq < 4 ? 0xffffffffu : 0u;
#pragma unroll
        for (int ks = 0; ks < 4; ks++) {
            const uint32_t qa = sb + SM_Q + ((gq & 1) * 64 + (gq & 2) * 16 + ks * 8 + t) * 4;
            bq[ks][0] = lds32(qa) & msk;
            bq[ks][1] = lds32(qa + 16) & msk;
        }
        float mx0 = -INFINITY, mx1 = -INFINITY;
        uint32_t rowaddr = sb + SM_K + (warp * 16 + (lane & 15)) * 128;
        const uint32_t xo = (lane >> 4) ^ (lane & 7);
        uint32_t sa = sb + SM_S + (warp * 8 + (lane >> 3)) * 4;
#pragma unroll 1
        for (int ch = 0; ch < 8; ch += 2) {
            uint32_t ka[2][4][4];
#pragma unroll
            for (int u = 0; u < 2; u++) {
                mbar_wait(BAR(IT_K + ch + u));
#pragma unroll
                for (int ks = 0; ks < 4; ks++) ldsm4(rowaddr + u * 16384 + (((2 * ks) ^ xo) << 4), ka[u][ks]);
            }
            float c[2][4];
#pragma unroll
            for (int u = 0; u < 2; u++) c[u][0] = c[u][1] = c[u][2] = c[u][3] = 0.f;
#pragma unroll
            for (int ks = 0; ks < 4; ks++)
#pragma unroll
                for (int u = 0; u < 2; u++)
                    mma16(c[u], ka[u][ks][0], ka[u][ks][1], ka[u][ks][2], ka[u][ks][3], bq[ks][0], bq[ks][1]);
            const float sc = 0.08838834764831845f;
#pragma unroll
            for (int u = 0; u < 2; u++) {
#pragma unroll
                for (int i = 0; i < 4; i++) c[u][i] = rb(rb(c[u][i] + __shfl_down_sync(0xffffffffu, c[u][i], 5)) * sc);
                if ((lane & 7) == 0) {
                    const uint32_t d = sa + u * 256;
                    stsf(d, c[u][0]); stsf(d + 2048, c[u][1]); stsf(d + 16, c[u][2]); stsf(d + 2064, c[u][3]);
                }
                mx0 = fmaxf(mx0, fmaxf(c[u][0], c[u][2]));
                mx1 = fmaxf(mx1, fmaxf(c[u][1], c[u][3]));
            }
            rowaddr += 32768; sa += 512;
        }
#pragma unroll
        for (int o = 8; o <= 16; o <<= 1) {
            mx0 = fmaxf(mx0, __shfl_xor_sync(0xffffffffu, mx0, o));
            mx1 = fmaxf(mx1, __shfl_xor_sync(0xffffffffu, mx1, o));
        }
        if (lane == 0) { stsf(sb + SM_SMALL + warp * 4, mx0); stsf(sb + SM_SMALL + 32 + warp * 4, mx1); }
        asm volatile("bar.sync 5, 256;" ::: "memory");
        if (tid == 0) { mbar_arrive(BAR(BF_K)); TS(6); }
        const uint32_t hd = warp >> 2;
        const float4 ma = ldsf4(sb + SM_SMALL + hd * 32), mb = ldsf4(sb + SM_SMALL + hd * 32 + 16);
        const float4 s4 = ldsf4(sb + SM_S + tid * 16);
        const float m = fmaxf(fmaxf(fmaxf(ma.x, ma.y), fmaxf(ma.z, ma.w)), fmaxf(fmaxf(mb.x, mb.y), fmaxf(mb.z, mb.w)));
        const float p0 = ex2((s4.x - m) * LOG2E), p1 = ex2((s4.y - m) * LOG2E), p2 = ex2((s4.z - m) * LOG2E), p3 = ex2((s4.w - m) * LOG2E);
        sts64(sb + SM_P + tid * 8, pack2(p0, p1), pack2(p2, p3));
        float l = (p0 + p1) + (p2 + p3);
#pragma unroll
        for (int o = 16; o > 0; o >>= 1) l += __shfl_xor_sync(0xffffffffu, l, o);
        if (lane == 0) { stsf(sb + SM_SMALL + 128 + warp * 4, l); stsf(sb + SM_SMALL + 160 + hd * 4, m); }
        asm volatile("bar.sync 5, 256;" ::: "memory");
        if (tid == 0) TS(7);
    }

    uint32_t wad[3];
#pragma unroll
    for (int i = 0; i < 3; i++) {
        const uint32_t T = warp * 3 + i, blk = T >> 2, ch = 2 * (T & 3) + ((lane >> 3) & 1);
        const uint32_t fr = ((lane & 7) + 8 * (lane >> 4)) * 9 + blk;
        wad[i] = sb + fr * 128 + ((ch ^ (fr & 7)) << 4);
        PIN(wad[i]);
    }
    if (warp < 4) {
        float c[2][4];
#pragma unroll
        for (int i = 0; i < 2; i++) c[i][0] = c[i][1] = c[i][2] = c[i][3] = 0.f;
        const uint32_t row = (lane & 7) + 8 * (lane >> 4);
        const uint32_t off = sb + SM_RING + row * 128 + (((2 * warp + ((lane >> 3) & 1)) ^ (lane & 7)) << 4);
        uint32_t pp = sb + SM_P + ((gq & 1) * 512 + t) * 2;
        const uint32_t mul = gq < 2 ? 1u : gq < 4 ? 65536u : 0u;
        float f0 = 0.f, f1 = 0.f;
        uint4* o_dst = box;
        uint32_t slot = 4;
#pragma unroll 1
        for (int ch = 0; ch < 8; ch++) {
            uint32_t bp[16];
#pragma unroll
            for (int i = 0; i < 16; i++) bp[i] = lds16(pp + i * 8) * mul;
            if (ch == 7) {
                asm volatile("bar.sync 3, 288;" ::: "memory");
                f0 = ldsf(sb + SM_SMALL + 176); f1 = ldsf(sb + SM_SMALL + 180);
                const uint32_t ro = grp * 8 + (t & 1) * 4 + warp;
                o_dst = box + (BX_O + ro * 512 + (lds32(sb + SM_XN + ro * 4) & 2) * 128 + rk * 16 + gq);
            }
            uint32_t base = off + slot * 16384;
            PIN(base);
            mbar_wait(BAR(IT_V + ch));
            uint32_t va[8][4];
#pragma unroll
            for (int ks = 0; ks < 8; ks++) ldsm4t(base + ks * 2048, va[ks]);
#pragma unroll
            for (int ks = 0; ks < 8; ks++) mma16(c[ks & 1], va[ks][0], va[ks][1], va[ks][2], va[ks][3], bp[2 * ks], bp[2 * ks + 1]);
            if (ch < 3 && lane == 0) mbar_arrive(BAR(BF_V0 + ch));
            slot = slot == 4 ? 0 : slot + 1;
            pp += 128;
        }
        if (t < 2) {
            st_msg(o_dst, __float_as_uint((c[0][0] + c[1][0]) * f0), __float_as_uint((c[0][1] + c[1][1]) * f1), 0u, tag);
            st_msg(o_dst + 8, __float_as_uint((c[0][2] + c[1][2]) * f0), __float_as_uint((c[0][3] + c[1][3]) * f1), 0u, tag);
        }
        if (tid == 0) TS(8);
    } else {
        if (warp == 4) {
            const uint32_t hd = lane & 1;
            const float m_own = ldsf(sb + SM_SMALL + 160 + hd * 4);
            const float4 l4 = ldsf4(sb + SM_SMALL + 128 + hd * 16);
            if (lane < 2) st_msg(box + BX_ML + cta * 2 + lane, __float_as_uint(m_own), __float_as_uint((l4.x + l4.y) + (l4.z + l4.w)), 0u, tag);
            const uint4 v = poll_msg(box + BX_ML + grp * 16 + (lane & 15), tag);
            const float ms = __uint_as_float(v.x);
            float M = ms;
#pragma unroll
            for (int o = 2; o <= 8; o <<= 1) M = fmaxf(M, __shfl_xor_sync(0xffffffffu, M, o));
            float L = __uint_as_float(v.y) * ex2((ms - M) * LOG2E);
#pragma unroll
            for (int o = 2; o <= 8; o <<= 1) L += __shfl_xor_sync(0xffffffffu, L, o);
            if (lane < 2) stsf(sb + SM_SMALL + 176 + lane * 4, ex2((m_own - M) * LOG2E) * rcp(L));
            __syncwarp();
            asm volatile("bar.arrive 3, 288;" ::: "memory");
        } else if (warp >= 8) {
#pragma unroll 1
            for (uint32_t i = tid - 64; i < 576; i += 128) {
                const uint4 v = poll_msg<200>(box + BX_MOD + i, tag);
                const uint32_t d = sb + SM_MOD + i * 12;
                sts32(d, v.x); sts32(d + 4, v.y); sts32(d + 8, v.z);
            }
            mbar_wait(BAR(IT_V));
            const uint32_t* side = reinterpret_cast<const uint32_t*>(box + BX_SIDE) + (tid - 256) * 2;
            uint32_t sp, so;
            unsigned n = 0;
#pragma unroll 1
            do { sp = ld_acq32(side); so = ld_acq32(side + 1); }
            while (__any_sync(0xffffffffu, ((sp ^ (tag << 1)) | (so ^ (tag << 1))) > 1u) && ++n < SPIN_MAX);
            sts32(sb + SM_XN + (tid - 256) * 4, (sp & 1) | ((so & 1) << 1));
            asm volatile("bar.arrive 3, 288;" ::: "memory");
            if (tid == 256) TS(18);
        }
        if (warp < 8) {
            const uint32_t d = (warp - 4) * 4 + t;
            const uint4* src = box + (BX_O + cta * 512 + (h_own & 2) * 128 + gq * 16 + d);
            const uint32_t od = sb + SM_O + d * 2;
            mbar_wait(BAR(IT_V + 7));
            const uint4 v = poll_msg(src, tag);
            if (tid == 128) TS(30);
            float o0 = __uint_as_float(v.x), o1 = __uint_as_float(v.y);
#pragma unroll
            for (int o = 4; o <= 16; o <<= 1) {
                o0 += __shfl_xor_sync(0xffffffffu, o0, o);
                o1 += __shfl_xor_sync(0xffffffffu, o1, o);
            }
            if (lane < 4) { sts16(od, f2b(o0)); sts16(od + 32, f2b(o1)); }
            if (tid == 128) TS(21);
        }
    }

    uint4* part_dst;
    const uint4* part_src = box + (BX_PART + cta * 512 + (h_own & 1) * 256 + lane);
    {
        uint32_t wa[3][8];
        mbar_wait(BAR(IT_WO));
        mbar_wait(BAR(IT_WO + 1));
#pragma unroll
        for (int i = 0; i < 3; i++) { ldsm4t(wad[i] + SM_WO, &wa[i][0]); ldsm4t(wad[i] + SM_WO + 16 * 1152, &wa[i][4]); }
        cbar();
        if (tid == 0) TS(9);
        const uint32_t b0 = lds32(ob), b1 = lds32(ob + 16), b2 = lds32(ob + 32), b3 = lds32(ob + 48);
        const uint32_t rp = warp * 8 + gq;
        part_dst = box + (BX_PART + rp * 512 + (lds32(sb + SM_XN + rp * 4) & 1) * 256 + cta * 2 + (t & 1));
        float c[3][4];
#pragma unroll
        for (int i = 0; i < 3; i++) {
            c[i][0] = c[i][1] = c[i][2] = c[i][3] = 0.f;
            mma16(c[i], wa[i][0], wa[i][1], wa[i][2], wa[i][3], b0, b1);
        }
#pragma unroll
        for (int i = 0; i < 3; i++) mma16(c[i], wa[i][4], wa[i][5], wa[i][6], wa[i][7], b2, b3);
        if (t < 2) st_msg(part_dst, __float_as_uint(t ? c[0][2] : c[0][0]), __float_as_uint(t ? c[1][2] : c[1][0]),
                          __float_as_uint(t ? c[2][2] : c[2][0]), tag);
        if (tid == 0) TS(10);
    }
    float r_x2 = 0.f, r_gb = 0.f;
    const uint32_t ma = sb + SM_MOD + lcol * 2;
    if (is_red) {
        const float ga = blo(lds16(ma + 4 * D));
        r_gb = blo(lds16(ma + 10 * D));
        uint2* dst = reinterpret_cast<uint2*>(box + BX_X2) + (cta * 2 + (lane & 1));
        const float sv = reduce_part(part_src, tag, lane TSPASS(23));
        r_x2 = rb(blo(x0) + rb(ga * rb(sv)));
        const uint32_t w = __float_as_uint(r_x2);
        const uint32_t w1 = __shfl_down_sync(0xffffffffu, w, 2), w2 = __shfl_down_sync(0xffffffffu, w, 4);
        if (lane < 2) {
            st_msg8(dst, (w >> 16) | w1, (w2 >> 16) | (tag << 16));
            st_msg8(dst + 512, (w >> 16) | w1, (w2 >> 16) | (tag << 16));
        }
        if (tid == 256) TS(11);
        __syncwarp();
        asm volatile("bar.arrive 5, 224;" ::: "memory");
    }
    uint32_t wb[5][6];
#define W1_LOAD() do { _Pragma("unroll") for (int n = 0; n < 4; n++) { \
        ldsm4t(sb + SM_W1 + r4 * 64 + ((n ^ ((lane >> 1) & 3)) << 4), &wb[n][0]); \
        ldsm2t(sb + SM_W1 + r2 * 64 + ((n ^ ((lane >> 1) & 3)) << 4), &wb[n][4]); } } while (0)
    mbar_wait(BAR(IT_W1X + (warp >> 2)));
    ldsm4t(sb + SM_W1X + r4 * 16, &wb[4][0]);
    ldsm2t(sb + SM_W1X + r2 * 16, &wb[4][4]);
    const bool pre1 = mbar_test(BAR(IT_W1 + (warp >> 2)));
    if (pre1) W1_LOAD();
    if (is_ln) {
        float c0 = rb(1.f + blo(lds16(ma + 8 * D))), c1 = rb(1.f + blo(lds16(ma + 8 * D + 32))), c2 = rb(1.f + blo(lds16(ma + 8 * D + 64)));
        float s0 = blo(lds16(ma + 6 * D)), s1 = blo(lds16(ma + 6 * D + 32)), s2 = blo(lds16(ma + 6 * D + 64));
        const uint2* src = reinterpret_cast<const uint2*>(box + BX_X2 + (h_own & 4) * 64) + li;
        const uint32_t yd = sb + SM_VEC + lcol * 2;
        uint2 v;
        unsigned n = 0;
        if (cta < 96) asm volatile("bar.sync 5, 224;" ::: "memory");
#pragma unroll 1
        do { v = ld_msg8(src); } while (__any_sync(0xffffffffu, (v.y >> 16) != (tag & 0xffffu)) && ++n < SPIN_MAX);
        if (tid == 64) TS(12);
        float3 y = layernorm3(make_float3(blo(v.x), bhi(v.x), blo(v.y)), sb + SM_SMALL, scr_w, lane);
        y = layernorm3(make_float3(rb(rb(y.x * c0) + s0), rb(rb(y.y * c1) + s1), rb(rb(y.z * c2) + s2)), sb + SM_SMALL + 64, scr_w + 64, lane);
        sts16(yd, __float_as_uint(y.x) >> 16); sts16(yd + 32, __float_as_uint(y.y) >> 16); sts16(yd + 64, __float_as_uint(y.z) >> 16);
        if (tid == 64) TS(22);
    }
    {
        const uint32_t ya = sb + SM_VEC + (warp * 24 + t) * 4;
        if (!pre1) {
            mbar_wait(BAR(IT_W1 + (warp >> 2)));
            W1_LOAD();
        }
        cbar();
        if (tid == 0) TS(13);
#pragma unroll
        for (int i = 0; i < 6; i++) a[i] = lds32(ya + i * 16);
        strip_mma_store<5>(a, wb, red_w, lane);
    }
    {
        uint32_t wa[3][10];
        if (warp < 2) {
            const float r = red_sum(red_r);
            const float u = rb(rb(r) + blo(x1));
            const float z = 1.5957691216057308f * (u + 0.044715f * u * u * u);
            const bool live = tid < 32 || ((tid >> 2) & 1) == (cta & 1);
            if (tid < 40) sts16(sb + SM_O + tid * 2, live ? f2b(u * sigm(z)) : 0u);
            asm volatile("bar.sync 6, %0;" ::"n"(NCT) : "memory");
        } else {
            asm volatile("bar.arrive 1, %0;" ::"n"(NCT) : "memory");
        }
        mbar_wait(BAR(IT_W2 + (lane & 1)));
        __syncwarp();
#pragma unroll
        for (int i = 0; i < 3; i++) { ldsm4t(wad[i] + SM_W2, &wa[i][0]); ldsm4t(wad[i] + SM_W2 + 16 * 1152, &wa[i][4]); }
        if (warp >= 2) asm volatile("bar.sync 6, %0;" ::"n"(NCT) : "memory");
        if (tid == 0) TS(14);
        const uint32_t b0 = lds32(ob), b1 = lds32(ob + 16), b2 = lds32(ob + 32), b3 = lds32(ob + 48), b4 = lds32(ob + 64);
        float c[3][4], e[3][4];
#pragma unroll
        for (int i = 0; i < 3; i++) {
            c[i][0] = c[i][1] = c[i][2] = c[i][3] = e[i][0] = e[i][1] = e[i][2] = e[i][3] = 0.f;
            mma16(c[i], wa[i][0], wa[i][1], wa[i][2], wa[i][3], b0, b1);
            mma16(e[i], wa[i][4], wa[i][5], wa[i][6], wa[i][7], b2, b3);
        }
        mbar_wait(BAR(IT_W2C));
        if (tid == 0) TS(15);
#pragma unroll
        for (int i = 0; i < 3; i++) ldsm2t(wad[i] + SM_W2 + 32 * 1152, &wa[i][8]);
#pragma unroll
        for (int i = 0; i < 3; i++) mma8(c[i], wa[i][8], wa[i][9], b4);
        if (t < 2) st_msg(part_dst, __float_as_uint(t ? c[0][2] + e[0][2] : c[0][0] + e[0][0]), __float_as_uint(t ? c[1][2] + e[1][2] : c[1][0] + e[1][0]),
                          __float_as_uint(t ? c[2][2] + e[2][2] : c[2][0] + e[2][0]), tag2);
        if (tid == 0) TS(16);
    }
    if (is_red) {
        __nv_bfloat16* op = P.out + lcol;
        const float sv = reduce_part(part_src, tag2, lane TSPASS(24));
        const uint32_t y = f2b(r_x2 + rb(r_gb * rb(rb(sv) + blo(x2))));
        if (lane < 6) asm volatile("st.global.u16 [%0], %1;" ::"l"(op), "r"(y) : "memory");
        if (cta == 0 && lane == 0) asm volatile("st.relaxed.gpu.global.u32 [%0], %1;" ::"l"(box + BX_EPOCH), "r"(epoch + 1) : "memory");
        if (tid == 256) TS(17);
    }
#undef BAR
}

typedef CUresult (*EncodeFn)(CUtensorMap*, CUtensorMapDataType, cuuint32_t, void*, const cuuint64_t*, const cuuint64_t*,
                             const cuuint32_t*, const cuuint32_t*, CUtensorMapInterleave, CUtensorMapSwizzle,
                             CUtensorMapL2promotion, CUtensorMapFloatOOBfill);

void make_map(EncodeFn enc, CUtensorMap* m, const void* base, uint64_t cols, uint64_t rows, uint32_t bc, uint32_t br,
              CUtensorMapSwizzle sw, int promo = 2) {
    cuuint64_t dims[2] = {cols, rows};
    cuuint64_t strides[1] = {cols * 2};
    cuuint32_t box[2] = {bc, br};
    cuuint32_t es[2] = {1, 1};
    enc(m, CU_TENSOR_MAP_DATA_TYPE_BFLOAT16, 2, const_cast<void*>(base), dims, strides, box, es,
        CU_TENSOR_MAP_INTERLEAVE_NONE, sw, (CUtensorMapL2promotion)promo, CU_TENSOR_MAP_FLOAT_OOB_FILL_NONE);
}

}

extern "C" void kernel_launch(void* const* d_in, const int* in_sizes, int n_in, void* d_out, int out_size) {
    (void)in_sizes; (void)n_in; (void)out_size;
    void* fn = nullptr;
    cudaDriverEntryPointQueryResult qr;
    cudaGetDriverEntryPoint("cuTensorMapEncodeTiled", &fn, cudaEnableDefault, &qr);
    EncodeFn enc = (EncodeFn)fn;

    Params P;
    make_map(enc, &P.m_wq, d_in[3], 4096, D, 32, 192, CU_TENSOR_MAP_SWIZZLE_64B);
    make_map(enc, &P.m_k, d_in[1], 64, (uint64_t)HKV * SK * 2, 64, 128, CU_TENSOR_MAP_SWIZZLE_128B);
    make_map(enc, &P.m_v, d_in[2], 64, (uint64_t)HKV * SK * 2, 64, 128, CU_TENSOR_MAP_SWIZZLE_128B);
    make_map(enc, &P.m_wo, d_in[4], 64, 4096 * 9, 64, 144, CU_TENSOR_MAP_SWIZZLE_128B);
    make_map(enc, &P.m_w1, d_in[6], FF, D, 32, 192, CU_TENSOR_MAP_SWIZZLE_64B);
    make_map(enc, &P.m_w1x, d_in[6], FF, D, 8, 192, CU_TENSOR_MAP_SWIZZLE_NONE);
    make_map(enc, &P.m_w2, d_in[8], 64, FF * 9, 64, 144, CU_TENSOR_MAP_SWIZZLE_128B);
    make_map(enc, &P.m_w2b, d_in[8], 64, FF * 9, 64, 72, CU_TENSOR_MAP_SWIZZLE_128B);
    P.x = (const __nv_bfloat16*)d_in[0];
    P.c = (const __nv_bfloat16*)d_in[10];
    P.b1 = (const __nv_bfloat16*)d_in[7];
    P.b2 = (const __nv_bfloat16*)d_in[9];
    P.wmod = (const __nv_bfloat16*)d_in[11];
    P.out = (__nv_bfloat16*)d_out;
    void* boxp = nullptr;
    cudaGetSymbolAddress(&boxp, g_box);
    P.box = (uint4*)(((uintptr_t)boxp + 8191) & ~(uintptr_t)8191);

    cudaFuncSetAttribute(fused_kernel, cudaFuncAttributeMaxDynamicSharedMemorySize, SM_TOTAL);
    fused_kernel<<<NCTA, NTHREADS, SM_TOTAL>>>(P);
}
```

```cpp
#include <cuda_runtime.h>
#include <cuda_bf16.h>
#include <cuda.h>
#include <stdint.h>

namespace {

constexpr int D = 576, HKV = 16, SK = 32768, WIN = 4096, FF = 4608;
constexpr int NATT = 128;
constexpr int NCTA = NATT;
constexpr int NRED = 96;
constexpr int NMOD = 108;
constexpr int NCW = 12;
constexpr int NCT = NCW * 32;
constexpr int NTHREADS = NCT + 64;

constexpr int SM_K = 0;
constexpr int SM_WO = 0;
constexpr int SM_W2 = 36864;
constexpr int SM_W1 = 92160;
constexpr int SM_RING = 131072;
constexpr int SM_W1X = SM_RING + 3 * 16384;
constexpr int SM_M = SM_RING;
constexpr int SM_WQ = SM_RING + 36864;
constexpr int SM_MISC = SM_RING + 5 * 16384;
constexpr int SM_MOD = SM_MISC;
constexpr int SM_VEC = SM_MOD + 2304;
constexpr int SM_XN = SM_VEC + 1152;
constexpr int SM_Q = SM_XN + 1152;
constexpr int SM_S = SM_Q + 512;
constexpr int SM_P = SM_S + 4096;
constexpr int SM_RED = SM_P + 2048;
constexpr int SM_SMALL = SM_RED + 2304;
constexpr int SM_O = SM_SMALL + 256;
constexpr int SM_BAR = SM_O + 128;
constexpr int SM_TOTAL = SM_BAR + 40 * 8;
static_assert(SM_TOTAL <= 232448, "smem");

enum { IT_M = 0, IT_WQ = 1, IT_K = 4, IT_V = 12, IT_WO = 20, IT_W2 = 22, IT_W1 = 24, IT_W2C = 27, IT_W1X = 28,
       BF_WQ = 29, BF_K = 30, BF_X = 31, BF_V0 = 32  , NBAR_USED = 35, NPOS = 28, IT_NONE = 63 };
#define PROBE_REPS 11
#define MOD_BACKOFF 150
#define SIDE_AT 1
#define PFHINT ".L2::128B"

enum { BX_X2 = 0,
       BX_O = 1024,
       BX_PART = BX_O + NATT * 512,
       BX_MOD = BX_PART + NRED * 512,
       BX_Q = BX_MOD + 864,
       BX_ML = BX_Q + NATT * 8,
       BX_SIDE = BX_ML + NATT * 2,
       BX_EPOCH = BX_SIDE + 32,
       BX_TOTAL = BX_EPOCH + 8 };
static_assert(BX_TOTAL * 16 <= (2 << 20), "mailboxes stay inside one 2 MB page");
__device__ uint4 g_box[(4 << 20) / 16];
__device__ __forceinline__ uint32_t half_of(uint32_t pair, uint32_t side) {
    constexpr uint32_t MASK = ((1u << 13) | (1u << 16) | (1u << 17) | (1u << 19)) >> 4;
    return pair + (((__popc(pair & MASK) ^ side) & 1u) << 8);
}

#define TS(i) do {} while (0)

constexpr unsigned SPIN_MAX = 1u << 22;
#define PIN(x) asm volatile("" : "+r"(x))
#define PIN64(x) asm volatile("" : "+l"(x))
#define PINF(x) asm volatile("" : "+f"(x))

__device__ __forceinline__ uint32_t smem_u32(const void* p) { return (uint32_t)__cvta_generic_to_shared(p); }
__device__ __forceinline__ void mbar_init(uint32_t bar, uint32_t cnt) {
    asm volatile("mbarrier.init.shared::cta.b64 [%0], %1;" ::"r"(bar), "r"(cnt) : "memory");
}
__device__ __forceinline__ void mbar_expect_tx(uint32_t bar, uint32_t bytes) {
    asm volatile("mbarrier.arrive.expect_tx.shared::cta.b64 _, [%0], %1;" ::"r"(bar), "r"(bytes) : "memory");
}
__device__ __forceinline__ void mbar_arrive(uint32_t bar) {
    asm volatile("mbarrier.arrive.shared::cta.b64 _, [%0];" ::"r"(bar) : "memory");
}
__device__ __forceinline__ void mbar_wait(uint32_t bar) {
    uint32_t ok;
    unsigned n = 0;
#pragma unroll 1
    do {
        asm volatile("{\n.reg .pred p;\nmbarrier.try_wait.parity.shared::cta.b64 p, [%1], 0;\nselp.u32 %0, 1, 0, p;\n}"
                     : "=r"(ok) : "r"(bar) : "memory");
    } while (!ok && ++n < SPIN_MAX);
}
__device__ __forceinline__ bool mbar_test(uint32_t bar) {
    uint32_t ok;
    asm volatile("{\n.reg .pred p;\nmbarrier.test_wait.parity.shared::cta.b64 p, [%1], 0;\nselp.u32 %0, 1, 0, p;\n}"
                 : "=r"(ok) : "r"(bar) : "memory");
    return __all_sync(0xffffffffu, ok);
}
__device__ __forceinline__ void tma2d(uint32_t dst, const CUtensorMap* map, int c0, int c1, uint32_t bar, uint64_t pol) {
    asm volatile("cp.async.bulk.tensor.2d.shared::cluster.global.mbarrier::complete_tx::bytes.L2::cache_hint [%0], [%1, {%3, %4}], [%2], %5;"
                 ::"r"(dst), "l"(map), "r"(bar), "r"(c0), "r"(c1), "l"(pol) : "memory");
}
__device__ __forceinline__ void cp16(uint32_t dst, const void* src) {
    asm volatile("cp.async.cg.shared.global" PFHINT " [%0], [%1], 16;" ::"r"(dst), "l"(src) : "memory");
}
__device__ __forceinline__ void cp_arrive(uint32_t bar) {
    asm volatile("cp.async.mbarrier.arrive.noinc.shared::cta.b64 [%0];" ::"r"(bar) : "memory");
}
__device__ __forceinline__ void cbar() { asm volatile("bar.sync 1, %0;" ::"n"(NCT) : "memory"); }

__device__ __forceinline__ uint32_t lds32(uint32_t a) { uint32_t v; asm volatile("ld.shared.u32 %0, [%1];" : "=r"(v) : "r"(a) : "memory"); return v; }
__device__ __forceinline__ uint32_t lds16(uint32_t a) { uint32_t v; asm volatile("ld.shared.u16 %0, [%1];" : "=r"(v) : "r"(a) : "memory"); return v; }
__device__ __forceinline__ float ldsf(uint32_t a) { float v; asm volatile("ld.shared.f32 %0, [%1];" : "=f"(v) : "r"(a) : "memory"); return v; }
__device__ __forceinline__ float4 ldsf4(uint32_t a) {
    float4 v;
    asm volatile("ld.shared.v4.f32 {%0,%1,%2,%3}, [%4];" : "=f"(v.x), "=f"(v.y), "=f"(v.z), "=f"(v.w) : "r"(a) : "memory");
    return v;
}
__device__ __forceinline__ void sts32(uint32_t a, uint32_t v) { asm volatile("st.shared.u32 [%0], %1;" ::"r"(a), "r"(v) : "memory"); }
__device__ __forceinline__ void sts16(uint32_t a, uint32_t v) { asm volatile("st.shared.u16 [%0], %1;" ::"r"(a), "r"(v) : "memory"); }
__device__ __forceinline__ void stsf(uint32_t a, float v) { asm volatile("st.shared.f32 [%0], %1;" ::"r"(a), "f"(v) : "memory"); }
__device__ __forceinline__ void sts64(uint32_t a, uint32_t x, uint32_t y) { asm volatile("st.shared.v2.u32 [%0], {%1,%2};" ::"r"(a), "r"(x), "r"(y) : "memory"); }

__device__ __forceinline__ void st_msg(uint4* p, uint32_t a, uint32_t b, uint32_t c, uint32_t d) {
    asm volatile("{\n.reg .b128 t;\n.reg .b64 lo, hi;\nmov.b64 lo, {%1, %2};\nmov.b64 hi, {%3, %4};\nmov.b128 t, {lo, hi};\n"
                 "st.relaxed.gpu.global.b128 [%0], t;\n}" ::"l"(p), "r"(a), "r"(b), "r"(c), "r"(d) : "memory");
}
__device__ __forceinline__ uint4 ld_msg(const uint4* p) {
    uint4 v;
    asm volatile("{\n.reg .b128 t;\n.reg .b64 lo, hi;\nld.relaxed.gpu.global.b128 t, [%4];\nmov.b128 {lo, hi}, t;\n"
                 "mov.b64 {%0, %1}, lo;\nmov.b64 {%2, %3}, hi;\n}" : "=r"(v.x), "=r"(v.y), "=r"(v.z), "=r"(v.w) : "l"(p) : "memory");
    return v;
}
template <int BACKOFF = 0>
__device__ __forceinline__ uint4 poll_msg(const uint4* p, uint32_t tag) {
    uint4 v;
    v.w = tag + 1;
    unsigned n = 0;
#pragma unroll 1
    do {
        if (BACKOFF && n) __nanosleep(BACKOFF);
        if (v.w != tag) v = ld_msg(p);
    } while (__any_sync(0xffffffffu, v.w != tag) && ++n < SPIN_MAX);
    return v;
}
__device__ __forceinline__ void st_msg8(uint2* p, uint32_t a, uint32_t b) {
    asm volatile("{\n.reg .b64 t;\nmov.b64 t, {%1, %2};\nst.relaxed.gpu.global.b64 [%0], t;\n}" ::"l"(p), "r"(a), "r"(b) : "memory");
}
__device__ __forceinline__ uint2 ld_msg8(const uint2* p) {
    uint2 v;
    asm volatile("{\n.reg .b64 t;\nld.relaxed.gpu.global.b64 t, [%2];\nmov.b64 {%0, %1}, t;\n}" : "=r"(v.x), "=r"(v.y) : "l"(p) : "memory");
    return v;
}
__device__ __forceinline__ uint32_t ldg16(const __nv_bfloat16* p) {
    uint32_t v;
    asm volatile("ld.global.nc.u16 %0, [%1];" : "=r"(v) : "l"(p));
    return v;
}

__device__ __forceinline__ void ldsm4(uint32_t a, uint32_t* r) {
    asm volatile("ldmatrix.sync.aligned.m8n8.x4.shared.b16 {%0,%1,%2,%3}, [%4];" : "=r"(r[0]), "=r"(r[1]), "=r"(r[2]), "=r"(r[3]) : "r"(a) : "memory");
}
__device__ __forceinline__ void ldsm4t(uint32_t a, uint32_t* r) {
    asm volatile("ldmatrix.sync.aligned.m8n8.x4.trans.shared.b16 {%0,%1,%2,%3}, [%4];" : "=r"(r[0]), "=r"(r[1]), "=r"(r[2]), "=r"(r[3]) : "r"(a) : "memory");
}
__device__ __forceinline__ void ldsm2t(uint32_t a, uint32_t* r) {
    asm volatile("ldmatrix.sync.aligned.m8n8.x2.trans.shared.b16 {%0,%1}, [%2];" : "=r"(r[0]), "=r"(r[1]) : "r"(a) : "memory");
}
__device__ __forceinline__ void mma16(float* c, uint32_t a0, uint32_t a1, uint32_t a2, uint32_t a3, uint32_t b0, uint32_t b1) {
    asm volatile("mma.sync.aligned.m16n8k16.row.col.f32.bf16.bf16.f32 {%0,%1,%2,%3}, {%4,%5,%6,%7}, {%8,%9}, {%0,%1,%2,%3};"
                 : "+f"(c[0]), "+f"(c[1]), "+f"(c[2]), "+f"(c[3]) : "r"(a0), "r"(a1), "r"(a2), "r"(a3), "r"(b0), "r"(b1));
}
__device__ __forceinline__ void mma8(float* c, uint32_t a0, uint32_t a1, uint32_t b0) {
    asm volatile("mma.sync.aligned.m16n8k8.row.col.f32.bf16.bf16.f32 {%0,%1,%2,%3}, {%4,%5}, {%6}, {%0,%1,%2,%3};"
                 : "+f"(c[0]), "+f"(c[1]), "+f"(c[2]), "+f"(c[3]) : "r"(a0), "r"(a1), "r"(b0));
}

__device__ __forceinline__ uint32_t pack2(float lo, float hi) {
    uint32_t r;
    asm("cvt.rn.bf16x2.f32 %0, %1, %2;" : "=r"(r) : "f"(hi), "f"(lo));
    return r;
}
__device__ __forceinline__ float rb(float x) { return __uint_as_float(pack2(0.f, x)); }
__device__ __forceinline__ uint32_t f2b(float x) { return pack2(x, 0.f); }
__device__ __forceinline__ float blo(uint32_t u) { return __uint_as_float(u << 16); }
__device__ __forceinline__ float bhi(uint32_t u) { return __uint_as_float(u & 0xffff0000u); }
__device__ __forceinline__ float ex2(float x) { float r; asm("ex2.approx.ftz.f32 %0, %1;" : "=f"(r) : "f"(x)); return r; }
__device__ __forceinline__ float rcp(float x) { float r; asm("rcp.approx.ftz.f32 %0, %1;" : "=f"(r) : "f"(x)); return r; }
constexpr float LOG2E = 1.4426950408889634f;
__device__ __forceinline__ float sigm(float x) { return rcp(1.f + ex2(-LOG2E * x)); }

__device__ __forceinline__ float3 layernorm3(float3 v, uint32_t scr, uint32_t scr_w, int lane) {
    float s = v.x + v.y + v.z, q = v.x * v.x + v.y * v.y + v.z * v.z;
#pragma unroll
    for (int o = 16; o > 0; o >>= 1) {
        s += __shfl_xor_sync(0xffffffffu, s, o);
        q += __shfl_xor_sync(0xffffffffu, q, o);
    }
    if (lane == 0) sts64(scr_w, __float_as_uint(s), __float_as_uint(q));
    asm volatile("bar.sync 4, 192;" ::: "memory");
    const float4 e0 = ldsf4(scr), e1 = ldsf4(scr + 16), e2 = ldsf4(scr + 32);
    const float mean = ((e0.x + e0.z) + (e1.x + e1.z) + (e2.x + e2.z)) * (1.0f / D);
    const float var = ((e0.y + e0.w) + (e1.y + e1.w) + (e2.y + e2.w)) * (1.0f / D) - mean * mean;
    const float mb = rb(mean);
    float den;
    asm("sqrt.approx.ftz.f32 %0, %1;" : "=f"(den) : "f"(rb(rb(fmaxf(var, 0.f)) + 1e-5f)));
    const float inv = rcp(rb(den));
    return make_float3(rb(rb(v.x - mb) * inv), rb(rb(v.y - mb) * inv), rb(rb(v.z - mb) * inv));
}

template <int NT>
__device__ __forceinline__ void strip_load(uint32_t p4, uint32_t p2, int x, uint32_t (&b)[NT][6]) {
#pragma unroll
    for (int n = 0; n < NT; n++) {
        ldsm4t(p4 + ((n ^ x) << 4), &b[n][0]);
        ldsm2t(p2 + ((n ^ x) << 4), &b[n][4]);
    }
}
__device__ __forceinline__ float red_sum(uint32_t red_r) {
    cbar();
    float v[NCW];
#pragma unroll
    for (int w = 0; w < NCW; w++) v[w] = ldsf(red_r + w * 160);
    return ((v[0] + v[1]) + (v[2] + v[3])) + ((v[4] + v[5]) + (v[6] + v[7])) + ((v[8] + v[9]) + (v[10] + v[11]));
}
template <int NT>
__device__ __forceinline__ void strip_mma_store(const uint32_t (&a)[6], const uint32_t (&b)[NT][6], uint32_t red_w, int lane) {
    float c[NT][4];
#pragma unroll
    for (int n = 0; n < NT; n++) c[n][0] = c[n][1] = c[n][2] = c[n][3] = 0.f;
#pragma unroll
    for (int k = 0; k < 3; k++)
#pragma unroll
        for (int n = 0; n < NT; n++) mma16(c[n], a[2 * k], a[2 * k], a[2 * k + 1], a[2 * k + 1], b[n][2 * k], b[n][2 * k + 1]);
    if (lane < 4) {
#pragma unroll
        for (int n = 0; n < NT; n++) sts64(red_w + n * 32, __float_as_uint(c[n][0]), __float_as_uint(c[n][1]));
    }
}
template <int NT>
__device__ __forceinline__ float strip_mma(const uint32_t (&a)[6], const uint32_t (&b)[NT][6], uint32_t red_w, uint32_t red_r, int lane) {
    strip_mma_store<NT>(a, b, red_w, lane);
    return red_sum(red_r);
}

#define TSARG
#define TSPASS(i)
__device__ __forceinline__ float reduce_part(const uint4* p, uint32_t tag, int lane TSARG) {
    uint4 v[8];
    bool pend;
    unsigned n = 0;
#pragma unroll 1
    do {
#pragma unroll
        for (int i = 0; i < 8; i++) v[i] = ld_msg(p + i * 32);
        pend = false;
#pragma unroll
        for (int i = 0; i < 8; i++) pend |= v[i].w != tag;
    } while (__any_sync(0xffffffffu, pend) && ++n < SPIN_MAX);
#define F(i, c) __uint_as_float(v[i].c)
    float s0 = ((F(0, x) + F(1, x)) + (F(2, x) + F(3, x))) + ((F(4, x) + F(5, x)) + (F(6, x) + F(7, x)));
    float s1 = ((F(0, y) + F(1, y)) + (F(2, y) + F(3, y))) + ((F(4, y) + F(5, y)) + (F(6, y) + F(7, y)));
    float s2 = ((F(0, z) + F(1, z)) + (F(2, z) + F(3, z))) + ((F(4, z) + F(5, z)) + (F(6, z) + F(7, z)));
#undef F
#pragma unroll
    for (int o = 16; o > 1; o >>= 1) {
        s0 += __shfl_xor_sync(0xffffffffu, s0, o);
        s1 += __shfl_xor_sync(0xffffffffu, s1, o);
        s2 += __shfl_xor_sync(0xffffffffu, s2, o);
    }
    return lane < 2 ? s0 : lane < 4 ? s1 : s2;
}

struct Params {
    uint32_t sched[30];
    uint32_t stagger;
    uint32_t pf_m;
    CUtensorMap m_wq, m_k, m_v, m_wo, m_w1, m_w2, m_w1x;
    __nv_bfloat16* out;
    unsigned long long* ts;
};

__global__ void __launch_bounds__(NTHREADS, 1)
fused_kernel(const __nv_bfloat16* __restrict__ p_wmod, const __nv_bfloat16* __restrict__ p_c, const __nv_bfloat16* __restrict__ p_x,
             uint4* const box, const __nv_bfloat16* __restrict__ p_b1, const __nv_bfloat16* __restrict__ p_b2,
             const __grid_constant__ Params P) {
    extern __shared__ __align__(1024) unsigned char smem[];
    uint32_t t_start;
    asm volatile("mov.u32 %0, %globaltimer_lo;" : "=r"(t_start));
    uint32_t tid = threadIdx.x, warp = tid >> 5, lane = tid & 31;
    uint32_t cta = blockIdx.x;
    const uint32_t sb = smem_u32(smem);
#define BAR(i) (sb + SM_BAR + (i) * 8)
    if (warp < NCW && cta < NMOD) {
        const uint32_t row = warp * 48 + (lane >> 2);
        const char* src = reinterpret_cast<const char*>(p_wmod) + (row * (6 * D * 2) + cta * 64 + (lane & 3) * 16);
        const uint32_t d = sb + SM_M + row * 64 + (((lane & 3) ^ ((lane >> 3) & 3)) << 4);
#pragma unroll
        for (int k = 0; k < 6; k++) cp16(d + k * 512, src + k * 8 * (6 * D * 2));
    }
    uint32_t grp = cta >> 3, rk = cta & 7;

    if (warp == NCW) {
        const uint32_t sc = P.sched[min(lane, 29u)], stagger = P.stagger;
        const int i = sc & 63;
        int mapi = 1, c0 = 0, c1, bytes = 16384, fbar = -1;
        uint32_t dst;
        if (i < IT_K) {
            mapi = 0; c0 = cta * 32; c1 = (i - IT_WQ) * 192; dst = SM_WQ + (i - IT_WQ) * 12288; bytes = 12288;
        } else if (i < IT_WO) {
            const int k = (i - IT_K) & 7;
            c1 = (grp * SK + (SK - WIN) + (k * 8 + rk) * 64) * 2;
            dst = SM_K + k * 16384;
            if (i >= IT_V) {
                mapi = 2; dst = SM_RING + (k < 5 ? k : k - 5) * 16384;
                fbar = k == 0 ? BF_WQ : k >= 5 ? BF_V0 + k - 5 : -1;
            }
        } else if (i < IT_W2) {
            mapi = 3; c1 = (grp * 256 + (i - IT_WO) * 128 + rk * 16) * 9; dst = SM_WO + (i - IT_WO) * 18432; bytes = 18432;
            fbar = BF_K;
        } else if (i < IT_W1) {
            mapi = 5; c1 = (cta * 32 + (i - IT_W2) * 16) * 9; dst = SM_W2 + (i - IT_W2) * 18432; bytes = 18432;
        } else if (i < IT_W2C) {
            mapi = 4; c0 = cta * 32; c1 = (i - IT_W1) * 192; dst = SM_W1 + (i - IT_W1) * 12288; bytes = 12288;
        } else if (i == IT_W2C) {
            mapi = 5; c1 = (4096 + (cta - NRED) * 16) * 9; dst = SM_W2 + 2 * 18432; bytes = cta >= NRED ? 18432 : 0;
        } else {
            mapi = 6; c0 = 4096 + (cta - NRED) * 16; c1 = 0; dst = SM_W1X; bytes = cta >= NRED ? 18432 : 0;
            fbar = BF_X;
        }
        uint64_t pol;
        asm volatile("createpolicy.fractional.L2::evict_first.b64 %0, 1.0;" : "=l"(pol));
        const uint32_t t_iss = t_start + (sc >> 16) + ((((sc >> 12) & 15) * ((cta + 32) & 127) * stagger) >> 10);
        const CUtensorMap* map = &P.m_wq + mapi;
        const uint32_t gates = ((sc >> 6) & 63) | ((uint32_t)(fbar & 63) << 8);
        if (lane == 0) TS(27);
        asm volatile("bar.sync 2, %0;" ::"n"(NTHREADS) : "memory");
        if (lane == 0) TS(28);
#pragma unroll 1
        for (int k = 0; k < NPOS; k++) {
            const uint32_t gk = __shfl_sync(0xffffffffu, gates, k);
            const uint32_t tk = __shfl_sync(0xffffffffu, t_iss, k);
            if ((gk & 63) != IT_NONE) mbar_wait(BAR(gk & 63));
            if ((gk >> 8) != IT_NONE) mbar_wait(BAR(gk >> 8));
            uint32_t now;
            unsigned n = 0;
            do { asm volatile("mov.u32 %0, %globaltimer_lo;" : "=r"(now)); } while ((int)(now - tk) < 0 && ++n < SPIN_MAX);
            if (lane == k && bytes) {
                const uint32_t bk = BAR(i);
                mbar_expect_tx(bk, bytes);
                tma2d(sb + dst, map, c0, c1, bk, pol);
                if (mapi == 6) { tma2d(sb + dst + 6144, map, c0, 192, bk, pol); tma2d(sb + dst + 12288, map, c0, 384, bk, pol); }
                TS(32 + k);
            }
            __syncwarp();
        }
        return;
    }

    if (warp > NCW) {
        if (lane == 0) {
#pragma unroll
            for (int i = 0; i < NBAR_USED; i++) mbar_init(BAR(i), i == IT_M ? NCT : i >= BF_X ? 4 : 1);
        }
        __syncwarp();
        asm volatile("bar.arrive 2, %0;" ::"n"(NTHREADS) : "memory");
        if (lane < 7) asm volatile("prefetch.tensormap [%0];" ::"l"(&P.m_wq + lane) : "memory");
        uint32_t epoch;
        asm volatile("ld.relaxed.gpu.global.u32 %0, [%1];" : "=r"(epoch) : "l"(box + BX_EPOCH) : "memory");
        lane = __shfl_sync(0xffffffffu, lane, lane); cta = __shfl_sync(0xffffffffu, cta, 0);
        const uint32_t rcol = min(48 * (cta >> 3) + 8 * min(lane, 5u) + (cta & 7), D - 1u);
        const uint32_t rx = ldg16(p_x + rcol), rb2 = ldg16(p_b2 + rcol);
        const uint32_t rb1 = ldg16(p_b1 + cta * 32 + lane), rb1x = ldg16(p_b1 + 4096 + (cta & 31) * 16 + (lane & 15));
        __nv_bfloat16* const op = P.out + rcol;
        uint2* const x2_dst = reinterpret_cast<uint2*>(box + half_of(BX_X2 + ((lane >> 3) & 1) * 512, lane >> 1) + ((lane >> 2) & 1) * 128) +
                              (cta * 2 + (lane & 1));
        if (cta < NRED && lane < 16) st_msg8(x2_dst, 0u, 0u);
        const uint32_t tag = epoch * 2 + 1;
        uint32_t side = 0;
        st_msg(box + half_of(BX_O + cta * 512, (lane >> 1) & 1) + 128 + (lane >> 2) * 16 + (lane & 1), 0u, 0u, 0u, 0u);
        mbar_wait(BAR(IT_M));
        if (lane == 0) {
            uint32_t best0 = 0xffffffffu, best1 = 0xffffffffu;
#pragma unroll 1
            for (uint32_t r = 0; r < PROBE_REPS * 2; r++) {
                uint32_t c0, c1 = 0;
                asm volatile("{\n.reg .pred p;\n.reg .u32 v;\nmov.u32 %0, %clock;\natom.relaxed.gpu.global.exch.b32 v, [%2], 0;\n"
                             "setp.ne.u32 p, v, 1;\n@p mov.u32 %1, %clock;\n}" : "=r"(c0), "+r"(c1)
                             : "l"(box + half_of(BX_O + cta * 512, r & 1) + 128 + ((r >> 1) & 7) * 16) : "memory");
                if (r & 1) best1 = min(best1, c1 - c0); else best0 = min(best0, c1 - c0);
                const uint32_t lo = min(best0, best1), hi = max(best0, best1);
                if (r >= 5 && lo < 380 && lo * 10 < hi * 8) break;
            }
            side = best1 < best0;
            asm volatile("st.relaxed.gpu.global.u32 [%0], %1;" ::"l"(reinterpret_cast<uint32_t*>(box + BX_SIDE) + cta),
                         "r"((tag << 1) | side) : "memory");
        }
        side = __shfl_sync(0xffffffffu, side, 0);
        const uint4* part_src = box + (half_of(BX_PART + min(cta, NRED - 1u) * 512, side) + lane);
        float ga, gb;
        {
            const uint4 va = poll_msg<200>(box + BX_MOD + (2 * D + rcol) / 4, tag), vb = poll_msg<200>(box + BX_MOD + (5 * D + rcol) / 4, tag);
            const uint32_t ua = rcol & 2 ? va.y : va.x, ub = rcol & 2 ? vb.y : vb.x;
            ga = rcol & 1 ? bhi(ua) : blo(ua);
            gb = rcol & 1 ? bhi(ub) : blo(ub);
        }
        float r_x2 = 0.f;
        if (cta < NRED) {
            mbar_wait(BAR(IT_WO + 1));
            const float sv = reduce_part(part_src, tag, lane TSPASS(23));
            r_x2 = rb(blo(rx) + rb(ga * rb(sv)));
            const uint32_t w = __float_as_uint(r_x2);
            const uint32_t w0 = __shfl_sync(0xffffffffu, w, lane & 1), w1 = __shfl_sync(0xffffffffu, w, (lane & 1) + 2),
                           w2 = __shfl_sync(0xffffffffu, w, (lane & 1) + 4);
            if (lane < 16) st_msg8(x2_dst, (w0 >> 16) | w1, (w2 >> 16) | (tag << 16));
            if (lane == 0) TS(11);
            __syncwarp();
            asm volatile("bar.arrive 9, 224;" ::: "memory");
        }
        {
            asm volatile("bar.sync 8, %0;" ::"n"(NCT + 32) : "memory");
            uint32_t hv[2];
#pragma unroll
            for (int k = 0; k < 2; k++) {
                const uint32_t ra = sb + SM_RED + (k ? 32 + (lane & 15) : lane) * 48;
                const float4 p0 = ldsf4(ra), p1 = ldsf4(ra + 16), p2 = ldsf4(ra + 32);
                const float r = ((p0.x + p0.y) + (p0.z + p0.w)) + ((p1.x + p1.y) + (p1.z + p1.w)) + ((p2.x + p2.y) + (p2.z + p2.w));
                const float u = rb(rb(r) + blo(k ? rb1x : rb1));
                const float z = 1.5957691216057308f * (u + 0.044715f * u * u * u);
                hv[k] = f2b(u * sigm(z));
            }
            sts16(sb + SM_O + lane * 2, hv[0]);
            if (lane < 16) sts16(sb + SM_O + 64 + lane * 2, hv[1]);
            __syncwarp();
            asm volatile("bar.arrive 6, %0;" ::"n"(NCT + 32) : "memory");
        }
        if (cta < NRED) {
            const float sv = reduce_part(part_src, tag + 1, lane TSPASS(24));
            const uint32_t y = f2b(r_x2 + rb(gb * rb(rb(sv) + blo(rb2))));
            if (lane < 6) asm volatile("st.global.u16 [%0], %1;" ::"l"(op), "r"(y) : "memory");
            if (cta == 0 && lane == 0) asm volatile("st.relaxed.gpu.global.u32 [%0], %1;" ::"l"(box + BX_EPOCH), "r"(epoch + 1) : "memory");
            if (lane == 0) TS(17);
        }
        return;
    }

    tid = __shfl_sync(0xffffffffu, tid, lane); cta = __shfl_sync(0xffffffffu, cta, 0);
    warp = tid >> 5; lane = tid & 31; grp = cta >> 3; rk = cta & 7;
    const uint32_t t = lane & 3, gq = lane >> 2;
    const uint32_t li = tid - 64;
    const bool is_ln = li < 192;
    const uint32_t lcol = is_ln ? 48 * (li >> 4) + 8 * (li & 1) + ((li >> 1) & 7) : 0;
    const uint32_t vi = warp * 24 + min(lane, 23u);
    uint32_t cv, epoch, x0, x1, x2;
    asm volatile("ld.global.nc.u32 %0, [%1];" : "=r"(cv) : "l"(reinterpret_cast<const uint32_t*>(p_c) + vi));
    asm volatile("ld.relaxed.gpu.global.u32 %0, [%1];" : "=r"(epoch) : "l"(box + BX_EPOCH) : "memory");
    x0 = ldg16(p_x + lcol); x1 = ldg16(p_x + lcol + 16); x2 = ldg16(p_x + lcol + 32);
    asm volatile("cp.async.commit_group;" ::: "memory");
    asm volatile("bar.sync 2, %0;" ::"n"(NTHREADS) : "memory");
    cp_arrive(BAR(IT_M));
    if (warp == 8) {
        const uint32_t idx = lane < 8 ? BX_MOD + cta * 8 + lane : lane < 16 ? BX_Q + cta * 8 + lane - 8 : BX_ML + cta * 2 + lane - 16;
        if (lane < 18 && (lane >= 8 || cta < NMOD)) st_msg(box + idx, 0u, 0u, 0u, 0u);
    }
    if (tid == 0) TS(20);
    uint32_t a[6];
    {
        PIN(cv);
        const float c0 = blo(cv), c1 = bhi(cv);
        const uint32_t av = pack2(c0 * sigm(c0), c1 * sigm(c1));
#pragma unroll
        for (int i = 0; i < 6; i++) a[i] = __shfl_sync(0xffffffffu, av, i * 4 + t);
    }
    const uint32_t scr_w = sb + SM_SMALL + (warp - 2) * 8;
    PIN(x0); PIN(x1); PIN(x2);
    if (is_ln) {
        const float3 xv = layernorm3(make_float3(blo(x0), blo(x1), blo(x2)), sb + SM_SMALL + 192, scr_w + 192, lane);
        sts16(sb + SM_XN + lcol * 2, __float_as_uint(xv.x) >> 16);
        sts16(sb + SM_XN + lcol * 2 + 32, __float_as_uint(xv.y) >> 16);
        sts16(sb + SM_XN + lcol * 2 + 64, __float_as_uint(xv.z) >> 16);
    }
    const uint32_t tag = epoch * 2 + 1, tag2 = epoch * 2 + 2;
    const uint32_t red_w = sb + SM_RED + warp * 160 + lane * 8, red_r = sb + SM_RED + min(tid, 39u) * 4;
    const uint32_t r4 = warp * 48 + lane, r2 = warp * 48 + 32 + (lane & 15);
    if (tid == 0) TS(1);

    asm volatile("cp.async.wait_group 0;" ::: "memory");
    __syncwarp();
    if (tid == 0) TS(19);
    const bool extra = cta >= NRED;
    const uint32_t w1row = warp * 48 + (lane & 7) + 8 * (lane >> 4);
#pragma unroll 1
    for (uint32_t ph = cta < NMOD ? 0 : 1; ph < 2; ph++) {
        if (ph) {
            cbar();
            if (tid == 0) TS(2);
            const uint32_t l24 = min(lane, 23u), sl = (l24 >= 12 ? 132 : 0) + warp * 12 + l24;
            const uint4 v = poll_msg<MOD_BACKOFF>(box + BX_MOD + sl, tag);
            sts64(sb + SM_MOD + sl * 8, v.x, v.y);
            __syncwarp();
            const uint32_t xn = lds32(sb + SM_XN + vi * 4), sa = lds32(sb + SM_MOD + vi * 4), ca = lds32(sb + SM_MOD + 1152 + vi * 4);
            const uint32_t one = pack2(1.f + blo(ca), 1.f + bhi(ca));
            const uint32_t pr = pack2(blo(xn) * blo(one), bhi(xn) * bhi(one));
            const uint32_t av = pack2(blo(pr) + blo(sa), bhi(pr) + bhi(sa));
#pragma unroll
            for (int i = 0; i < 6; i++) a[i] = __shfl_sync(0xffffffffu, av, i * 4 + t);
            if (tid == 0) TS(3);
            mbar_wait(BAR(IT_WQ + (warp >> 2)));
        }
        uint32_t b[4][6];
        strip_load<4>(sb + SM_M + ph * 36864 + r4 * 64, sb + SM_M + ph * 36864 + r2 * 64, (lane >> 1) & 3, b);
        const float r = strip_mma<4>(a, b, red_w, red_r, lane);
        if (warp == 0) {
            sts16(sb + SM_O + lane * 2, f2b(r));
            __syncwarp();
            if (lane < 8) st_msg(box + (ph ? BX_Q : BX_MOD) + cta * 8 + lane, lds32(sb + SM_O + lane * 8), lds32(sb + SM_O + lane * 8 + 4), 0u, tag);
        }
    }
    if (tid == 0) { mbar_arrive(BAR(BF_WQ)); TS(4); }
    if (li < 64) {
        const uint4 v = poll_msg(box + BX_Q + grp * 64 + li, tag);
        sts64(sb + SM_Q + li * 8, v.x, v.y);
    }
    cbar();
    if (tid == 0) TS(5);
    const uint32_t ob = sb + SM_O + t * 4;

    if (warp < 8) {
        uint32_t bq[4][2];
        const uint32_t msk = gq < 4 ? 0xffffffffu : 0u;
#pragma unroll
        for (int ks = 0; ks < 4; ks++) {
            const uint32_t qa = sb + SM_Q + ((gq & 1) * 64 + (gq & 2) * 16 + ks * 8 + t) * 4;
            bq[ks][0] = lds32(qa) & msk;
            bq[ks][1] = lds32(qa + 16) & msk;
        }
        float mx0 = -INFINITY, mx1 = -INFINITY;
        uint32_t rowaddr = sb + SM_K + (warp * 16 + (lane & 15)) * 128;
        const uint32_t xo = (lane >> 4) ^ (lane & 7);
        uint32_t sa = sb + SM_S + (warp * 8 + (lane >> 3)) * 4;
#pragma unroll 1
        for (int ch = 0; ch < 8; ch += 2) {
            uint32_t ka[2][4][4];
#pragma unroll
            for (int u = 0; u < 2; u++) {
                mbar_wait(BAR(IT_K + ch + u));
#pragma unroll
                for (int ks = 0; ks < 4; ks++) ldsm4(rowaddr + u * 16384 + (((2 * ks) ^ xo) << 4), ka[u][ks]);
            }
            float c[2][4];
#pragma unroll
            for (int u = 0; u < 2; u++) c[u][0] = c[u][1] = c[u][2] = c[u][3] = 0.f;
#pragma unroll
            for (int ks = 0; ks < 4; ks++)
#pragma unroll
                for (int u = 0; u < 2; u++)
                    mma16(c[u], ka[u][ks][0], ka[u][ks][1], ka[u][ks][2], ka[u][ks][3], bq[ks][0], bq[ks][1]);
            const float sc = 0.08838834764831845f;
#pragma unroll
            for (int u = 0; u < 2; u++) {
#pragma unroll
                for (int i = 0; i < 4; i++) c[u][i] = rb(rb(c[u][i] + __shfl_down_sync(0xffffffffu, c[u][i], 5)) * sc);
                if ((lane & 7) == 0) {
                    const uint32_t d = sa + u * 256;
                    stsf(d, c[u][0]); stsf(d + 2048, c[u][1]); stsf(d + 16, c[u][2]); stsf(d + 2064, c[u][3]);
                }
                mx0 = fmaxf(mx0, fmaxf(c[u][0], c[u][2]));
                mx1 = fmaxf(mx1, fmaxf(c[u][1], c[u][3]));
            }
            rowaddr += 32768; sa += 512;
        }
#pragma unroll
        for (int o = 8; o <= 16; o <<= 1) {
            mx0 = fmaxf(mx0, __shfl_xor_sync(0xffffffffu, mx0, o));
            mx1 = fmaxf(mx1, __shfl_xor_sync(0xffffffffu, mx1, o));
        }
        if (lane == 0) { stsf(sb + SM_SMALL + warp * 4, mx0); stsf(sb + SM_SMALL + 32 + warp * 4, mx1); }
        asm volatile("bar.sync 5, 256;" ::: "memory");
        if (tid == 0) { mbar_arrive(BAR(BF_K)); TS(6); }
        const uint32_t hd = warp >> 2;
        const float4 ma = ldsf4(sb + SM_SMALL + hd * 32), mb = ldsf4(sb + SM_SMALL + hd * 32 + 16);
        const float4 s4 = ldsf4(sb + SM_S + tid * 16);
        const float m = fmaxf(fmaxf(fmaxf(ma.x, ma.y), fmaxf(ma.z, ma.w)), fmaxf(fmaxf(mb.x, mb.y), fmaxf(mb.z, mb.w)));
        const float p0 = ex2((s4.x - m) * LOG2E), p1 = ex2((s4.y - m) * LOG2E), p2 = ex2((s4.z - m) * LOG2E), p3 = ex2((s4.w - m) * LOG2E);
        sts64(sb + SM_P + tid * 8, pack2(p0, p1), pack2(p2, p3));
        float l = (p0 + p1) + (p2 + p3);
#pragma unroll
        for (int o = 16; o > 0; o >>= 1) l += __shfl_xor_sync(0xffffffffu, l, o);
        if (lane == 0) { stsf(sb + SM_SMALL + 128 + warp * 4, l); stsf(sb + SM_SMALL + 160 + hd * 4, m); }
        asm volatile("bar.sync 5, 256;" ::: "memory");
        if (tid == 0) TS(7);
    }

    uint32_t wad[3];
#pragma unroll
    for (int i = 0; i < 3; i++) {
        const uint32_t T = warp * 3 + i, blk = T >> 2, ch = 2 * (T & 3) + ((lane >> 3) & 1);
        const uint32_t fr = ((lane & 7) + 8 * (lane >> 4)) * 9 + blk;
        wad[i] = sb + fr * 128 + ((ch ^ (fr & 7)) << 4);
        PIN(wad[i]);
    }
    if (warp < 4) {
        float c[2][4];
#pragma unroll
        for (int i = 0; i < 2; i++) c[i][0] = c[i][1] = c[i][2] = c[i][3] = 0.f;
        const uint32_t row = (lane & 7) + 8 * (lane >> 4);
        const uint32_t off = sb + SM_RING + row * 128 + (((2 * warp + ((lane >> 3) & 1)) ^ (lane & 7)) << 4);
        uint32_t pp = sb + SM_P + ((gq & 1) * 512 + t) * 2;
        const uint32_t mul = gq < 2 ? 1u : gq < 4 ? 65536u : 0u;
        float f0 = 0.f, f1 = 0.f;
        uint4* o_dst = box;
        uint32_t slot = 0;
#pragma unroll 1
        for (int ch = 0; ch < 8; ch++) {
            uint32_t bp[16];
#pragma unroll
            for (int i = 0; i < 16; i++) bp[i] = lds16(pp + i * 8) * mul;
            if (ch == 7) {
                asm volatile("bar.sync 3, %0;" ::"n"(NCT) : "memory");
                f0 = ldsf(sb + SM_SMALL + 176); f1 = ldsf(sb + SM_SMALL + 180);
                const uint32_t ro = grp * 8 + (t & 1) * 4 + warp;
                o_dst = box + (half_of(BX_O + ro * 512, lds32(sb + SM_XN + ro * 4)) + rk * 16 + gq);
            }
            uint32_t base = off + slot * 16384;
            PIN(base);
            mbar_wait(BAR(IT_V + ch));
            uint32_t va[8][4];
#pragma unroll
            for (int ks = 0; ks < 8; ks++) ldsm4t(base + ks * 2048, va[ks]);
#pragma unroll
            for (int ks = 0; ks < 8; ks++) mma16(c[ks & 1], va[ks][0], va[ks][1], va[ks][2], va[ks][3], bp[2 * ks], bp[2 * ks + 1]);
            if ((ch < 3 || ch == 4) && lane == 0) mbar_arrive(BAR(ch == 4 ? BF_X : BF_V0 + ch));
            slot = slot == 4 ? 0 : slot + 1;
            pp += 128;
        }
        if (t < 2) {
            st_msg(o_dst, __float_as_uint((c[0][0] + c[1][0]) * f0), __float_as_uint((c[0][1] + c[1][1]) * f1), 0u, tag);
            st_msg(o_dst + 8, __float_as_uint((c[0][2] + c[1][2]) * f0), __float_as_uint((c[0][3] + c[1][3]) * f1), 0u, tag);
        }
        if (tid == 0) TS(8);
    } else {
        if (warp == 4) {
            const uint32_t hd = lane & 1;
            const float m_own = ldsf(sb + SM_SMALL + 160 + hd * 4);
            const float4 l4 = ldsf4(sb + SM_SMALL + 128 + hd * 16);
            if (lane < 2) st_msg(box + BX_ML + cta * 2 + lane, __float_as_uint(m_own), __float_as_uint((l4.x + l4.y) + (l4.z + l4.w)), 0u, tag);
            const uint4 v = poll_msg(box + BX_ML + grp * 16 + (lane & 15), tag);
            const float ms = __uint_as_float(v.x);
            float M = ms;
#pragma unroll
            for (int o = 2; o <= 8; o <<= 1) M = fmaxf(M, __shfl_xor_sync(0xffffffffu, M, o));
            float L = __uint_as_float(v.y) * ex2((ms - M) * LOG2E);
#pragma unroll
            for (int o = 2; o <= 8; o <<= 1) L += __shfl_xor_sync(0xffffffffu, L, o);
            if (lane < 2) stsf(sb + SM_SMALL + 176 + lane * 4, ex2((m_own - M) * LOG2E) * rcp(L));
        } else if (warp >= 8) {
#pragma unroll 1
            for (uint32_t i = tid - 256; i < 288; i += 128) {
                const uint4 v = poll_msg<200>(box + BX_MOD + 432 + i, tag);
                sts64(sb + SM_MOD + i * 8, v.x, v.y);
            }
            mbar_wait(BAR(IT_V + SIDE_AT));
            const uint32_t u = tid - 256;
            const uint32_t* side = reinterpret_cast<const uint32_t*>(box + BX_SIDE) + u;
            uint32_t sp;
            unsigned n = 0;
#pragma unroll 1
            do {
                if (n) __nanosleep(500);
                asm volatile("ld.relaxed.gpu.global.u32 %0, [%1];" : "=r"(sp) : "l"(side) : "memory");
            } while (__any_sync(0xffffffffu, (sp ^ (tag << 1)) > 1u) && ++n < SPIN_MAX);
            sts32(sb + SM_XN + u * 4, sp & 1);
            asm volatile("bar.sync 7, 128;" ::: "memory");
            if (!(P.pf_m & 4)) {
#pragma unroll
                for (int k = 0; k < 2; k++) {
                    const uint32_t rp = k * 64 + (u >> 1);
                    if (rp < NRED) st_msg(box + (half_of(BX_PART + rp * 512, lds32(sb + SM_XN + rp * 4)) + cta * 2 + (u & 1)), 0u, 0u, 0u, 0u);
                }
            }
            const uint32_t ro = grp * 8 + (u >> 4);
            if (!(P.pf_m & 8)) st_msg(box + (half_of(BX_O + ro * 512, lds32(sb + SM_XN + ro * 4)) + rk * 16 + (u & 15)), 0u, 0u, 0u, 0u);
            asm volatile("bar.arrive 3, %0;" ::"n"(NCT) : "memory");
            if (tid == 256) TS(18);
        }
        if (warp < 8) {
            const uint32_t d = (warp - 4) * 4 + t;
            asm volatile("bar.sync 3, %0;" ::"n"(NCT) : "memory");
            const uint4* src = box + (half_of(BX_O + cta * 512, lds32(sb + SM_XN + cta * 4)) + gq * 16 + d);
            const uint32_t od = sb + SM_O + d * 2;
            mbar_wait(BAR(IT_V + 7));
            const uint4 v = poll_msg(src, tag);
            if (tid == 128) TS(30);
            float o0 = __uint_as_float(v.x), o1 = __uint_as_float(v.y);
#pragma unroll
            for (int o = 4; o <= 16; o <<= 1) {
                o0 += __shfl_xor_sync(0xffffffffu, o0, o);
                o1 += __shfl_xor_sync(0xffffffffu, o1, o);
            }
            if (lane < 4) { sts16(od, f2b(o0)); sts16(od + 32, f2b(o1)); }
            if (tid == 128) TS(21);
        }
    }

    uint4* const part_dst = box + (half_of(BX_PART + (warp * 8 + gq) * 512, lds32(sb + SM_XN + (warp * 8 + gq) * 4)) + cta * 2 + (t & 1));
    const uint32_t my_side = lds32(sb + SM_XN + cta * 4);
    {
        uint32_t wa[3][8];
        mbar_wait(BAR(IT_WO));
#pragma unroll
        for (int i = 0; i < 3; i++) ldsm4t(wad[i] + SM_WO, &wa[i][0]);
        const bool pre0 = mbar_test(BAR(IT_WO + 1));
        if (pre0) {
#pragma unroll
            for (int i = 0; i < 3; i++) ldsm4t(wad[i] + SM_WO + 16 * 1152, &wa[i][4]);
        }
        cbar();
        if (tid == 0) TS(9);
        const uint32_t b0 = lds32(ob), b1 = lds32(ob + 16), b2 = lds32(ob + 32), b3 = lds32(ob + 48);
        float c[3][4];
#pragma unroll
        for (int i = 0; i < 3; i++) {
            c[i][0] = c[i][1] = c[i][2] = c[i][3] = 0.f;
            mma16(c[i], wa[i][0], wa[i][1], wa[i][2], wa[i][3], b0, b1);
        }
        if (!pre0) {
            mbar_wait(BAR(IT_WO + 1));
#pragma unroll
            for (int i = 0; i < 3; i++) ldsm4t(wad[i] + SM_WO + 16 * 1152, &wa[i][4]);
        }
#pragma unroll
        for (int i = 0; i < 3; i++) mma16(c[i], wa[i][4], wa[i][5], wa[i][6], wa[i][7], b2, b3);
        if (t < 2) st_msg(part_dst, __float_as_uint(t ? c[0][2] : c[0][0]), __float_as_uint(t ? c[1][2] : c[1][0]),
                          __float_as_uint(t ? c[2][2] : c[2][0]), tag);
        if (tid == 0) TS(10);
    }
    uint32_t wb[6][4], wx[3][4];
    {
        const uint32_t hi = (lane >> 3) & 1, sw = (lane >> 1) & 3;
        mbar_wait(BAR((lane & 1) && extra ? IT_W1X : IT_W1 + (warp >> 2)));
        __syncwarp();
#pragma unroll
        for (int k = 0; k < 3; k++) {
            if (extra) ldsm4t(sb + SM_W1X + (w1row + k * 16) * 32 + hi * 16, wx[k]);
            ldsm4t(sb + SM_W1 + (w1row + k * 16) * 64 + ((hi ^ sw) << 4), wb[k * 2]);
            ldsm4t(sb + SM_W1 + (w1row + k * 16) * 64 + (((2 + hi) ^ sw) << 4), wb[k * 2 + 1]);
        }
    }
    if (is_ln) {
        const uint32_t ma = sb + SM_MOD + lcol * 2;
        float c0 = rb(1.f + blo(lds16(ma + 2 * D))), c1 = rb(1.f + blo(lds16(ma + 2 * D + 32))), c2 = rb(1.f + blo(lds16(ma + 2 * D + 64)));
        float s0 = blo(lds16(ma)), s1 = blo(lds16(ma + 32)), s2 = blo(lds16(ma + 64));
        const uint2* src = reinterpret_cast<const uint2*>(box + half_of(BX_X2 + (cta & 2) * 256, my_side) + (cta & 1) * 128) + li;
        const uint32_t yd = sb + SM_VEC + lcol * 2;
        uint2 v;
        unsigned n = 0;
        if (cta < NRED) asm volatile("bar.sync 9, 224;" ::: "memory");
#pragma unroll 1
        do { v = ld_msg8(src); } while (__any_sync(0xffffffffu, (v.y >> 16) != (tag & 0xffffu)) && ++n < SPIN_MAX);
        if (tid == 64) TS(12);
        float3 y = layernorm3(make_float3(blo(v.x), bhi(v.x), blo(v.y)), sb + SM_SMALL, scr_w, lane);
        y = layernorm3(make_float3(rb(rb(y.x * c0) + s0), rb(rb(y.y * c1) + s1), rb(rb(y.z * c2) + s2)), sb + SM_SMALL + 64, scr_w + 64, lane);
        sts16(yd, __float_as_uint(y.x) >> 16); sts16(yd + 32, __float_as_uint(y.y) >> 16); sts16(yd + 64, __float_as_uint(y.z) >> 16);
        if (tid == 64) TS(22);
    }
    {
        const uint32_t ya = sb + SM_VEC + (warp * 24 + t) * 4;
        const uint32_t rd = sb + SM_RED + (t * 16 + gq) * 48 + warp * 4;
        cbar();
        if (tid == 0) TS(13);
#pragma unroll
        for (int i = 0; i < 6; i++) a[i] = lds32(ya + i * 16);
        float c[3][4];
#pragma unroll
        for (int j = 0; j < 3; j++) c[j][0] = c[j][1] = c[j][2] = c[j][3] = 0.f;
#pragma unroll
        for (int k = 0; k < 3; k++) {
#pragma unroll
            for (int j = 0; j < 2; j++) mma16(c[j], wb[k * 2 + j][0], wb[k * 2 + j][1], wb[k * 2 + j][2], wb[k * 2 + j][3], a[2 * k], a[2 * k + 1]);
            if (extra) mma16(c[2], wx[k][0], wx[k][1], wx[k][2], wx[k][3], a[2 * k], a[2 * k + 1]);
        }
        if (t < 3) {
            stsf(rd, t == 0 ? c[0][0] : t == 1 ? c[1][0] : c[2][0]);
            stsf(rd + 8 * 48, t == 0 ? c[0][2] : t == 1 ? c[1][2] : c[2][2]);
        }
        asm volatile("bar.arrive 8, %0;" ::"n"(NCT + 32) : "memory");
    }
    {
        uint32_t wa[3][12];
        mbar_wait(BAR((lane & 1) && extra ? IT_W2C : IT_W2));
        __syncwarp();
#pragma unroll
        for (int i = 0; i < 3; i++) {
            ldsm4t(wad[i] + SM_W2, &wa[i][0]);
            if (extra) ldsm4t(wad[i] + SM_W2 + 32 * 1152, &wa[i][8]);
        }
        const bool pre = mbar_test(BAR(IT_W2 + 1));
        if (pre) {
#pragma unroll
            for (int i = 0; i < 3; i++) ldsm4t(wad[i] + SM_W2 + 16 * 1152, &wa[i][4]);
        }
        asm volatile("bar.sync 6, %0;" ::"n"(NCT + 32) : "memory");
        if (tid == 0) TS(14);
        uint32_t b[6];
#pragma unroll
        for (int i = 0; i < 6; i++) b[i] = lds32(ob + i * 16);
        float c[3][4], e[3][4], f[3][4];
#pragma unroll
        for (int i = 0; i < 3; i++) {
#pragma unroll
            for (int j = 0; j < 4; j++) c[i][j] = e[i][j] = f[i][j] = 0.f;
            mma16(c[i], wa[i][0], wa[i][1], wa[i][2], wa[i][3], b[0], b[1]);
            if (extra) mma16(e[i], wa[i][8], wa[i][9], wa[i][10], wa[i][11], b[4], b[5]);
        }
        if (!pre) {
            mbar_wait(BAR(IT_W2 + 1));
#pragma unroll
            for (int i = 0; i < 3; i++) ldsm4t(wad[i] + SM_W2 + 16 * 1152, &wa[i][4]);
        }
        if (tid == 0) TS(15);
#pragma unroll
        for (int i = 0; i < 3; i++) mma16(f[i], wa[i][4], wa[i][5], wa[i][6], wa[i][7], b[2], b[3]);
        float r[3];
#pragma unroll
        for (int i = 0; i < 3; i++) r[i] = t ? (c[i][2] + e[i][2]) + f[i][2] : (c[i][0] + e[i][0]) + f[i][0];
        if (t < 2) st_msg(part_dst, __float_as_uint(r[0]), __float_as_uint(r[1]), __float_as_uint(r[2]), tag2);
        if (tid == 0) TS(16);
    }
#undef BAR
}

typedef CUresult (*EncodeFn)(CUtensorMap*, CUtensorMapDataType, cuuint32_t, void*, const cuuint64_t*, const cuuint64_t*,
                             const cuuint32_t*, const cuuint32_t*, CUtensorMapInterleave, CUtensorMapSwizzle,
                             CUtensorMapL2promotion, CUtensorMapFloatOOBfill);

void make_map(EncodeFn enc, CUtensorMap* m, const void* base, uint64_t cols, uint64_t rows, uint32_t bc, uint32_t br,
              CUtensorMapSwizzle sw, int promo = 2) {
    cuuint64_t dims[2] = {cols, rows};
    cuuint64_t strides[1] = {cols * 2};
    cuuint32_t box[2] = {bc, br};
    cuuint32_t es[2] = {1, 1};
    enc(m, CU_TENSOR_MAP_DATA_TYPE_BFLOAT16, 2, const_cast<void*>(base), dims, strides, box, es,
        CU_TENSOR_MAP_INTERLEAVE_NONE, sw, (CUtensorMapL2promotion)promo, CU_TENSOR_MAP_FLOAT_OOB_FILL_NONE);
}

#define PROMO_X 1
#define PROMO_S 2
#define PROMO_F 3
struct Tune { int t0, rate, stagger, gap, rate2, win, win2, pf_m; char order[40], stag[40]; };
Tune g_tune = {-1420, 2450, 670, 250, 2600, 4, 4, 0, "abcKKKKKKKKVVVVVVVVOOxdefXYX", "8888888888888888888448888888"};
void make_schedule(Params& P) {
    const Tune& T = g_tune;
    int nk = 0, nv = 0, no = 0, nx = 0, n = 0, hist[40], nh = 0;
    bool after = false;
    double t = T.t0 + 31104 * 100.0 / T.rate;
    hist[nh++] = IT_M;
    for (const char* c = T.order; *c && n < NPOS; c++) {
        int item, bytes;
        switch (*c) {
            case 'a': case 'b': case 'c': item = IT_WQ + (*c - 'a'); bytes = 12288; break;
            case 'K': item = IT_K + nk++; bytes = 16384; break;
            case 'V': item = IT_V + nv++; bytes = 16384; break;
            case 'O': item = IT_WO + no++; bytes = 18432; break;
            case 'd': case 'e': case 'f': item = IT_W1 + (*c - 'd'); bytes = 12288; break;
            case 'X': item = IT_W2 + nx++; bytes = 18432; break;
            case 'x': item = IT_W1X; bytes = 4608; break;
            default: item = IT_W2C; bytes = 4608; break;
        }
        t += bytes * 100.0 / (after ? T.rate2 : T.rate);
        const int win = after ? T.win2 : T.win;
        const int gate = nh >= win ? hist[nh - win] : IT_NONE;
        const int sg = T.stag[n] - '0';
        const int tt = (int)(t + (8 - sg) * T.stagger / 16.0);
        P.sched[n] = item | (gate << 6) | (sg << 12) | ((tt > 0 ? tt : 0) << 16);
        n++;
        if (bytes > 8192) hist[nh++] = item;
        if (no == 2 && nv == 8 && !after) { after = true; t += T.gap; }
    }
    for (; n < 30; n++) P.sched[n] = IT_NONE | (IT_NONE << 6);
    P.stagger = T.stagger;
    P.pf_m = T.pf_m;
}

}

extern "C" void kernel_launch(void* const* d_in, const int* in_sizes, int n_in, void* d_out, int out_size) {
    (void)in_sizes; (void)n_in; (void)out_size;
    void* fn = nullptr;
    cudaDriverEntryPointQueryResult qr;
    cudaGetDriverEntryPoint("cuTensorMapEncodeTiled", &fn, cudaEnableDefault, &qr);
    EncodeFn enc = (EncodeFn)fn;

    Params P;
    make_map(enc, &P.m_wq, d_in[3], 4096, D, 32, 192, CU_TENSOR_MAP_SWIZZLE_64B, PROMO_S);
    make_map(enc, &P.m_k, d_in[1], 64, (uint64_t)HKV * SK * 2, 64, 128, CU_TENSOR_MAP_SWIZZLE_128B, PROMO_F);
    make_map(enc, &P.m_v, d_in[2], 64, (uint64_t)HKV * SK * 2, 64, 128, CU_TENSOR_MAP_SWIZZLE_128B, PROMO_F);
    make_map(enc, &P.m_wo, d_in[4], 64, 4096 * 9, 64, 144, CU_TENSOR_MAP_SWIZZLE_128B, PROMO_F);
    make_map(enc, &P.m_w1, d_in[6], FF, D, 32, 192, CU_TENSOR_MAP_SWIZZLE_64B, PROMO_S);
    make_map(enc, &P.m_w1x, d_in[6], FF, D, 16, 192, CU_TENSOR_MAP_SWIZZLE_NONE, PROMO_X);
    make_map(enc, &P.m_w2, d_in[8], 64, FF * 9, 64, 144, CU_TENSOR_MAP_SWIZZLE_128B, PROMO_F);
    P.out = (__nv_bfloat16*)d_out;
    make_schedule(P);
    void* boxp = nullptr;
    cudaGetSymbolAddress(&boxp, g_box);
    uint4* box = (uint4*)(((uintptr_t)boxp + (2 << 20) - 1) & ~(uintptr_t)((2 << 20) - 1));

    cudaFuncSetAttribute(fused_kernel, cudaFuncAttributeMaxDynamicSharedMemorySize, SM_TOTAL);
    fused_kernel<<<NCTA, NTHREADS, SM_TOTAL>>>((const __nv_bfloat16*)d_in[11], (const __nv_bfloat16*)d_in[10], (const __nv_bfloat16*)d_in[0],
                                               box, (const __nv_bfloat16*)d_in[7], (const __nv_bfloat16*)d_in[9], P);
}
```

```cpp
#include <cuda_runtime.h>
#include <cuda_bf16.h>
#include <cuda.h>
#include <stdint.h>

namespace {

constexpr int D = 576, HKV = 16, SK = 32768, WIN = 4096, FF = 4608;
constexpr int NATT = 128;
constexpr int NCTA = NATT;
constexpr int NRED = 96;
constexpr int NMOD = 108;
constexpr int NCW = 12;
constexpr int NCT = NCW * 32;
constexpr int NTHREADS = NCT + 64;

constexpr int SM_K = 0;
constexpr int SM_WO = 0;
constexpr int SM_W2 = 36864;
constexpr int SM_W1 = 92160;
constexpr int SM_RING = 131072;
constexpr int SM_W1X = SM_RING + 3 * 16384;
constexpr int SM_M = SM_RING;
constexpr int SM_WQ = SM_RING + 36864;
constexpr int SM_MISC = SM_RING + 5 * 16384;
constexpr int SM_MOD = SM_MISC;
constexpr int SM_VEC = SM_MOD + 2304;
constexpr int SM_XN = SM_VEC + 1152;
constexpr int SM_Q = SM_XN + 1152;
constexpr int SM_S = SM_Q + 512;
constexpr int SM_P = SM_S + 4096;
constexpr int SM_RED = SM_P + 2048;
constexpr int SM_SMALL = SM_RED + 2304;
constexpr int SM_O = SM_SMALL + 256;
constexpr int SM_BAR = SM_O + 128;
constexpr int SM_TOTAL = SM_BAR + 40 * 8;
static_assert(SM_TOTAL <= 232448, "smem");

enum { IT_M = 0, IT_WQ = 1, IT_K = 4, IT_V = 12, IT_WO = 20, IT_W2 = 22, IT_W1 = 24, IT_W2C = 27, IT_W1X = 28,
       BF_WQ = 29, BF_K = 30, BF_X = 31, BF_V0 = 32  , NBAR_USED = 35, NPOS = 28, IT_NONE = 63 };

enum { BX_X2 = 0,
       BX_O = 1024,
       BX_PART = BX_O + NATT * 512,
       BX_MOD = BX_PART + NRED * 512,
       BX_Q = BX_MOD + 864,
       BX_ML = BX_Q + NATT * 8,
       BX_SIDE = BX_ML + NATT * 2,
       BX_EPOCH = BX_SIDE + 32,
       BX_TOTAL = BX_EPOCH + 8 };
static_assert(BX_TOTAL * 16 <= (2 << 20), "mailboxes stay inside one 2 MB page");
__device__ uint4 g_box[(4 << 20) / 16];
__device__ __forceinline__ uint32_t half_of(uint32_t pair, uint32_t side) {
    constexpr uint32_t MASK = ((1u << 13) | (1u << 16) | (1u << 17) | (1u << 19)) >> 4;
    return pair + (((__popc(pair & MASK) ^ side) & 1u) << 8);
}

#define TS(i) do {} while (0)

constexpr unsigned SPIN_MAX = 1u << 21;
#define PIN(x) asm volatile("" : "+r"(x))

__device__ __forceinline__ uint32_t smem_u32(const void* p) { return (uint32_t)__cvta_generic_to_shared(p); }
__device__ __forceinline__ void mbar_init(uint32_t bar, uint32_t cnt) {
    asm volatile("mbarrier.init.shared::cta.b64 [%0], %1;" ::"r"(bar), "r"(cnt) : "memory");
}
__device__ __forceinline__ void mbar_expect_tx(uint32_t bar, uint32_t bytes) {
    asm volatile("mbarrier.arrive.expect_tx.shared::cta.b64 _, [%0], %1;" ::"r"(bar), "r"(bytes) : "memory");
}
__device__ __forceinline__ void mbar_arrive(uint32_t bar) {
    asm volatile("mbarrier.arrive.shared::cta.b64 _, [%0];" ::"r"(bar) : "memory");
}
__device__ __forceinline__ void mbar_wait(uint32_t bar) {
    uint32_t ok;
    unsigned n = 0;
#pragma unroll 1
    do {
        asm volatile("{\n.reg .pred p;\nmbarrier.try_wait.parity.shared::cta.b64 p, [%1], 0, 1000;\nselp.u32 %0, 1, 0, p;\n}"
                     : "=r"(ok) : "r"(bar) : "memory");
    } while (!ok && ++n < SPIN_MAX);
}
__device__ __forceinline__ bool mbar_test(uint32_t bar) {
    uint32_t ok;
    asm volatile("{\n.reg .pred p;\nmbarrier.test_wait.parity.shared::cta.b64 p, [%1], 0;\nselp.u32 %0, 1, 0, p;\n}"
                 : "=r"(ok) : "r"(bar) : "memory");
    return __all_sync(0xffffffffu, ok);
}
__device__ __forceinline__ void tma2d(uint32_t dst, const CUtensorMap* map, int c0, int c1, uint32_t bar, uint64_t pol) {
    asm volatile("cp.async.bulk.tensor.2d.shared::cluster.global.mbarrier::complete_tx::bytes.L2::cache_hint [%0], [%1, {%3, %4}], [%2], %5;"
                 ::"r"(dst), "l"(map), "r"(bar), "r"(c0), "r"(c1), "l"(pol) : "memory");
}
__device__ __forceinline__ void cp16(uint32_t dst, const void* src) {
    asm volatile("cp.async.cg.shared.global.L2::128B [%0], [%1], 16;" ::"r"(dst), "l"(src) : "memory");
}
__device__ __forceinline__ void cp_arrive(uint32_t bar) {
    asm volatile("cp.async.mbarrier.arrive.noinc.shared::cta.b64 [%0];" ::"r"(bar) : "memory");
}
__device__ __forceinline__ void cbar() { asm volatile("bar.sync 1, %0;" ::"n"(NCT) : "memory"); }

__device__ __forceinline__ uint32_t lds32(uint32_t a) { uint32_t v; asm volatile("ld.shared.u32 %0, [%1];" : "=r"(v) : "r"(a) : "memory"); return v; }
__device__ __forceinline__ uint32_t lds16(uint32_t a) { uint32_t v; asm volatile("ld.shared.u16 %0, [%1];" : "=r"(v) : "r"(a) : "memory"); return v; }
__device__ __forceinline__ float ldsf(uint32_t a) { float v; asm volatile("ld.shared.f32 %0, [%1];" : "=f"(v) : "r"(a) : "memory"); return v; }
__device__ __forceinline__ float4 ldsf4(uint32_t a) {
    float4 v;
    asm volatile("ld.shared.v4.f32 {%0,%1,%2,%3}, [%4];" : "=f"(v.x), "=f"(v.y), "=f"(v.z), "=f"(v.w) : "r"(a) : "memory");
    return v;
}
__device__ __forceinline__ void sts32(uint32_t a, uint32_t v) { asm volatile("st.shared.u32 [%0], %1;" ::"r"(a), "r"(v) : "memory"); }
__device__ __forceinline__ void sts16(uint32_t a, uint32_t v) { asm volatile("st.shared.u16 [%0], %1;" ::"r"(a), "r"(v) : "memory"); }
__device__ __forceinline__ void stsf(uint32_t a, float v) { asm volatile("st.shared.f32 [%0], %1;" ::"r"(a), "f"(v) : "memory"); }
__device__ __forceinline__ void sts64(uint32_t a, uint32_t x, uint32_t y) { asm volatile("st.shared.v2.u32 [%0], {%1,%2};" ::"r"(a), "r"(x), "r"(y) : "memory"); }

__device__ __forceinline__ void st_msg(uint4* p, uint32_t a, uint32_t b, uint32_t c, uint32_t d) {
    asm volatile("{\n.reg .b128 t;\n.reg .b64 lo, hi;\nmov.b64 lo, {%1, %2};\nmov.b64 hi, {%3, %4};\nmov.b128 t, {lo, hi};\n"
                 "st.relaxed.gpu.global.b128 [%0], t;\n}" ::"l"(p), "r"(a), "r"(b), "r"(c), "r"(d) : "memory");
}
__device__ __forceinline__ uint4 ld_msg(const uint4* p) {
    uint4 v;
    asm volatile("{\n.reg .b128 t;\n.reg .b64 lo, hi;\nld.relaxed.gpu.global.b128 t, [%4];\nmov.b128 {lo, hi}, t;\n"
                 "mov.b64 {%0, %1}, lo;\nmov.b64 {%2, %3}, hi;\n}" : "=r"(v.x), "=r"(v.y), "=r"(v.z), "=r"(v.w) : "l"(p) : "memory");
    return v;
}
template <int BACKOFF = 0>
__device__ __forceinline__ uint4 poll_msg(const uint4* p, uint32_t tag) {
    uint4 v;
    v.w = tag + 1;
    unsigned n = 0;
#pragma unroll 1
    do {
        if (BACKOFF && n) __nanosleep(BACKOFF);
        if (v.w != tag) v = ld_msg(p);
    } while (__any_sync(0xffffffffu, v.w != tag) && ++n < SPIN_MAX);
    return v;
}
__device__ __forceinline__ void st_msg8(uint2* p, uint32_t a, uint32_t b) {
    asm volatile("{\n.reg .b64 t;\nmov.b64 t, {%1, %2};\nst.relaxed.gpu.global.b64 [%0], t;\n}" ::"l"(p), "r"(a), "r"(b) : "memory");
}
__device__ __forceinline__ uint2 ld_msg8(const uint2* p) {
    uint2 v;
    asm volatile("{\n.reg .b64 t;\nld.relaxed.gpu.global.b64 t, [%2];\nmov.b64 {%0, %1}, t;\n}" : "=r"(v.x), "=r"(v.y) : "l"(p) : "memory");
    return v;
}
__device__ __forceinline__ uint32_t ldg16(const __nv_bfloat16* p) {
    uint32_t v;
    asm volatile("ld.global.nc.u16 %0, [%1];" : "=r"(v) : "l"(p));
    return v;
}

__device__ __forceinline__ void ldsm4(uint32_t a, uint32_t* r) {
    asm volatile("ldmatrix.sync.aligned.m8n8.x4.shared.b16 {%0,%1,%2,%3}, [%4];" : "=r"(r[0]), "=r"(r[1]), "=r"(r[2]), "=r"(r[3]) : "r"(a) : "memory");
}
__device__ __forceinline__ void ldsm4t(uint32_t a, uint32_t* r) {
    asm volatile("ldmatrix.sync.aligned.m8n8.x4.trans.shared.b16 {%0,%1,%2,%3}, [%4];" : "=r"(r[0]), "=r"(r[1]), "=r"(r[2]), "=r"(r[3]) : "r"(a) : "memory");
}
__device__ __forceinline__ void ldsm2t(uint32_t a, uint32_t* r) {
    asm volatile("ldmatrix.sync.aligned.m8n8.x2.trans.shared.b16 {%0,%1}, [%2];" : "=r"(r[0]), "=r"(r[1]) : "r"(a) : "memory");
}
__device__ __forceinline__ void mma16(float* c, uint32_t a0, uint32_t a1, uint32_t a2, uint32_t a3, uint32_t b0, uint32_t b1) {
    asm volatile("mma.sync.aligned.m16n8k16.row.col.f32.bf16.bf16.f32 {%0,%1,%2,%3}, {%4,%5,%6,%7}, {%8,%9}, {%0,%1,%2,%3};"
                 : "+f"(c[0]), "+f"(c[1]), "+f"(c[2]), "+f"(c[3]) : "r"(a0), "r"(a1), "r"(a2), "r"(a3), "r"(b0), "r"(b1));
}

__device__ __forceinline__ uint32_t pack2(float lo, float hi) {
    uint32_t r;
    asm("cvt.rn.bf16x2.f32 %0, %1, %2;" : "=r"(r) : "f"(hi), "f"(lo));
    return r;
}
__device__ __forceinline__ float rb(float x) { return __uint_as_float(pack2(0.f, x)); }
__device__ __forceinline__ uint32_t f2b(float x) { return pack2(x, 0.f); }
__device__ __forceinline__ float blo(uint32_t u) { return __uint_as_float(u << 16); }
__device__ __forceinline__ float bhi(uint32_t u) { return __uint_as_float(u & 0xffff0000u); }
__device__ __forceinline__ float ex2(float x) { float r; asm("ex2.approx.ftz.f32 %0, %1;" : "=f"(r) : "f"(x)); return r; }
__device__ __forceinline__ float rcp(float x) { float r; asm("rcp.approx.ftz.f32 %0, %1;" : "=f"(r) : "f"(x)); return r; }
constexpr float LOG2E = 1.4426950408889634f;
__device__ __forceinline__ float sigm(float x) { return rcp(1.f + ex2(-LOG2E * x)); }

__device__ __forceinline__ float3 layernorm3(float3 v, uint32_t scr, uint32_t scr_w, int lane) {
    float s = v.x + v.y + v.z, q = v.x * v.x + v.y * v.y + v.z * v.z;
#pragma unroll
    for (int o = 16; o > 0; o >>= 1) {
        s += __shfl_xor_sync(0xffffffffu, s, o);
        q += __shfl_xor_sync(0xffffffffu, q, o);
    }
    if (lane == 0) sts64(scr_w, __float_as_uint(s), __float_as_uint(q));
    asm volatile("bar.sync 4, 192;" ::: "memory");
    const float4 e0 = ldsf4(scr), e1 = ldsf4(scr + 16), e2 = ldsf4(scr + 32);
    const float mean = ((e0.x + e0.z) + (e1.x + e1.z) + (e2.x + e2.z)) * (1.0f / D);
    const float var = ((e0.y + e0.w) + (e1.y + e1.w) + (e2.y + e2.w)) * (1.0f / D) - mean * mean;
    const float mb = rb(mean);
    float den;
    asm("sqrt.approx.ftz.f32 %0, %1;" : "=f"(den) : "f"(rb(rb(fmaxf(var, 0.f)) + 1e-5f)));
    const float inv = rcp(rb(den));
    return make_float3(rb(rb(v.x - mb) * inv), rb(rb(v.y - mb) * inv), rb(rb(v.z - mb) * inv));
}

template <int NT>
__device__ __forceinline__ void strip_load(uint32_t p4, uint32_t p2, int x, uint32_t (&b)[NT][6]) {
#pragma unroll
    for (int n = 0; n < NT; n++) {
        ldsm4t(p4 + ((n ^ x) << 4), &b[n][0]);
        ldsm2t(p2 + ((n ^ x) << 4), &b[n][4]);
    }
}
__device__ __forceinline__ float red_sum(uint32_t red_r) {
    cbar();
    float v[NCW];
#pragma unroll
    for (int w = 0; w < NCW; w++) v[w] = ldsf(red_r + w * 160);
    return ((v[0] + v[1]) + (v[2] + v[3])) + ((v[4] + v[5]) + (v[6] + v[7])) + ((v[8] + v[9]) + (v[10] + v[11]));
}
template <int NT>
__device__ __forceinline__ void strip_mma_store(const uint32_t (&a)[6], const uint32_t (&b)[NT][6], uint32_t red_w, int lane) {
    float c[NT][4];
#pragma unroll
    for (int n = 0; n < NT; n++) c[n][0] = c[n][1] = c[n][2] = c[n][3] = 0.f;
#pragma unroll
    for (int k = 0; k < 3; k++)
#pragma unroll
        for (int n = 0; n < NT; n++) mma16(c[n], a[2 * k], a[2 * k], a[2 * k + 1], a[2 * k + 1], b[n][2 * k], b[n][2 * k + 1]);
    if (lane < 4) {
#pragma unroll
        for (int n = 0; n < NT; n++) sts64(red_w + n * 32, __float_as_uint(c[n][0]), __float_as_uint(c[n][1]));
    }
}
template <int NT>
__device__ __forceinline__ float strip_mma(const uint32_t (&a)[6], const uint32_t (&b)[NT][6], uint32_t red_w, uint32_t red_r, int lane) {
    strip_mma_store<NT>(a, b, red_w, lane);
    return red_sum(red_r);
}

#define TSARG
#define TSPASS(i)
template <int N>
__device__ __forceinline__ void poll_slots(const uint4* p, uint32_t tag, uint4 (&v)[N]) {
    uint32_t pend = (1u << N) - 1;
    unsigned n = 0;
#pragma unroll 1
    do {
#pragma unroll
        for (int i = 0; i < N; i++) if (pend & (1u << i)) v[i] = ld_msg(p + i * 32);
        uint32_t m = 0;
#pragma unroll
        for (int i = 0; i < N; i++) m |= v[i].w != tag ? 1u << i : 0u;
        pend = __reduce_or_sync(0xffffffffu, m);
    } while (pend && ++n < SPIN_MAX);
}
__device__ __forceinline__ float reduce_part(const uint4* p, uint32_t tag, int lane TSARG) {
    uint4 v[8];
    poll_slots<8>(p, tag, v);
#define F(i, c) __uint_as_float(v[i].c)
    float s0 = ((F(0, x) + F(1, x)) + (F(2, x) + F(3, x))) + ((F(4, x) + F(5, x)) + (F(6, x) + F(7, x)));
    float s1 = ((F(0, y) + F(1, y)) + (F(2, y) + F(3, y))) + ((F(4, y) + F(5, y)) + (F(6, y) + F(7, y)));
    float s2 = ((F(0, z) + F(1, z)) + (F(2, z) + F(3, z))) + ((F(4, z) + F(5, z)) + (F(6, z) + F(7, z)));
#undef F
#pragma unroll
    for (int o = 16; o > 1; o >>= 1) {
        s0 += __shfl_xor_sync(0xffffffffu, s0, o);
        s1 += __shfl_xor_sync(0xffffffffu, s1, o);
        s2 += __shfl_xor_sync(0xffffffffu, s2, o);
    }
    return lane < 2 ? s0 : lane < 4 ? s1 : s2;
}

struct Params {
    uint32_t sched[NPOS];
    uint32_t stagger;
    uint32_t probe_deadline;
    const __nv_bfloat16* b2;
    CUtensorMap m_wq, m_k, m_v, m_wo, m_w1, m_w2, m_w1x;
};

__global__ void __launch_bounds__(NTHREADS, 1)
fused_kernel(const __nv_bfloat16* __restrict__ p_wmod, const __nv_bfloat16* __restrict__ p_c, const __nv_bfloat16* __restrict__ p_x,
             uint4* const box, const __nv_bfloat16* __restrict__ p_b1, __nv_bfloat16* __restrict__ p_out,
             const __grid_constant__ Params P) {
    extern __shared__ __align__(1024) unsigned char smem[];
    uint32_t t_start;
    asm volatile("mov.u32 %0, %globaltimer_lo;" : "=r"(t_start));
    uint32_t tid = threadIdx.x, warp = tid >> 5, lane = tid & 31;
    uint32_t cta = blockIdx.x;
    const uint32_t sb = smem_u32(smem);
#define BAR(i) (sb + SM_BAR + (i) * 8)
    if (warp < NCW && cta < NMOD) {
        const uint32_t row = warp * 48 + (lane >> 2);
        const char* src = reinterpret_cast<const char*>(p_wmod) + (row * (6 * D * 2) + cta * 64 + (lane & 3) * 16);
        const uint32_t d = sb + SM_M + row * 64 + (((lane & 3) ^ ((lane >> 3) & 3)) << 4);
#pragma unroll
        for (int k = 0; k < 6; k++) cp16(d + k * 512, src + k * 8 * (6 * D * 2));
    }
    uint32_t grp = cta >> 3, rk = cta & 7;

    if (warp == NCW) {
        const uint32_t sc = P.sched[min(lane, NPOS - 1u)], stagger = P.stagger;
        const int i = sc & 63;
        int mapi = 1, c0 = 0, c1, bytes = 16384, fbar = -1;
        uint32_t dst;
        if (i < IT_K) {
            mapi = 0; c0 = cta * 32; c1 = (i - IT_WQ) * 192; dst = SM_WQ + (i - IT_WQ) * 12288; bytes = 12288;
        } else if (i < IT_WO) {
            const int k = (i - IT_K) & 7;
            c1 = (grp * SK + (SK - WIN) + ((k >> 1) * 16 + rk * 2 + (k & 1)) * 64) * 2;
            dst = SM_K + k * 16384;
            if (i >= IT_V) {
                mapi = 2; dst = SM_RING + (k < 5 ? k : k - 5) * 16384;
                fbar = k == 0 ? BF_WQ : k >= 5 ? BF_V0 + k - 5 : -1;
            }
        } else if (i < IT_W2) {
            mapi = 3; c1 = (grp * 256 + (i - IT_WO) * 128 + rk * 16) * 9; dst = SM_WO + (i - IT_WO) * 18432; bytes = 18432;
            fbar = BF_K;
        } else if (i < IT_W1) {
            mapi = 5; c1 = (cta * 32 + (i - IT_W2) * 16) * 9; dst = SM_W2 + (i - IT_W2) * 18432; bytes = 18432;
        } else if (i < IT_W2C) {
            mapi = 4; c0 = cta * 32; c1 = (i - IT_W1) * 192; dst = SM_W1 + (i - IT_W1) * 12288; bytes = 12288;
        } else if (i == IT_W2C) {
            mapi = 5; c1 = (4096 + (cta - NRED) * 16) * 9; dst = SM_W2 + 2 * 18432; bytes = cta >= NRED ? 18432 : 0;
        } else {
            mapi = 6; c0 = 4096 + (cta - NRED) * 16; c1 = 0; dst = SM_W1X; bytes = cta >= NRED ? 18432 : 0;
            fbar = BF_X;
        }
        uint64_t pol;
        asm volatile("createpolicy.fractional.L2::evict_first.b64 %0, 1.0;" : "=l"(pol));
        const uint32_t t_iss = t_start + (sc >> 16) + ((((sc >> 12) & 15) * ((cta + 32) & 127) * stagger) >> 10);
        const CUtensorMap* map = &P.m_wq + mapi;
        const uint32_t gates = ((sc >> 6) & 63) | ((uint32_t)(fbar & 63) << 8);
        if (lane == 0) TS(27);
        asm volatile("bar.sync 2, %0;" ::"n"(NTHREADS) : "memory");
        if (lane == 0) TS(28);
#pragma unroll 1
        for (int k = 0; k < NPOS; k++) {
            const uint32_t gk = __shfl_sync(0xffffffffu, gates, k);
            const uint32_t tk = __shfl_sync(0xffffffffu, t_iss, k);
            if ((gk & 63) != IT_NONE) mbar_wait(BAR(gk & 63));
            if ((gk >> 8) != IT_NONE) mbar_wait(BAR(gk >> 8));
            uint32_t now;
            unsigned n = 0;
            do { asm volatile("mov.u32 %0, %globaltimer_lo;" : "=r"(now)); } while ((int)(now - tk) < 0 && ++n < SPIN_MAX);
            if (lane == k && bytes) {
                const uint32_t bk = BAR(i);
                mbar_expect_tx(bk, bytes);
                tma2d(sb + dst, map, c0, c1, bk, pol);
                if (mapi == 6) { tma2d(sb + dst + 6144, map, c0, 192, bk, pol); tma2d(sb + dst + 12288, map, c0, 384, bk, pol); }
                TS(32 + k);
            }
            __syncwarp();
        }
        return;
    }

    if (warp > NCW) {
        if (lane == 0) {
#pragma unroll
            for (int i = 0; i < NBAR_USED; i++) mbar_init(BAR(i), i == IT_M ? NCT : i >= BF_X ? 4 : 1);
        }
        __syncwarp();
        asm volatile("bar.arrive 2, %0;" ::"n"(NTHREADS) : "memory");
        st_msg(box + half_of(BX_O + cta * 512, (lane >> 1) & 1) + 128 + (lane >> 2) * 16 + (lane & 1), 0u, 0u, 0u, 0u);
        uint32_t epoch;
        asm volatile("ld.relaxed.gpu.global.u32 %0, [%1];" : "=r"(epoch) : "l"(box + BX_EPOCH) : "memory");
        if (lane < 7) asm volatile("prefetch.tensormap [%0];" ::"l"(&P.m_wq + lane) : "memory");
        lane = __shfl_sync(0xffffffffu, lane, lane); cta = __shfl_sync(0xffffffffu, cta, 0);
        uint32_t side = 0;
        if (lane == 0) {
            uint32_t best0 = 0xffffffffu, best1 = 0xffffffffu;
#pragma unroll 1
            for (uint32_t r = 0; r < 80; r++) {
                uint32_t c0, c1 = 0;
                asm volatile("{\n.reg .pred p;\n.reg .u32 v;\nmov.u32 %0, %clock;\natom.relaxed.gpu.global.exch.b32 v, [%2], 0;\n"
                             "setp.ne.u32 p, v, 1;\n@p mov.u32 %1, %clock;\n}" : "=r"(c0), "+r"(c1)
                             : "l"(box + half_of(BX_O + cta * 512, r & 1) + 128 + ((r >> 1) & 7) * 16) : "memory");
                if (r & 1) best1 = min(best1, c1 - c0); else best0 = min(best0, c1 - c0);
                const uint32_t lo = min(best0, best1), hi = max(best0, best1);
                uint32_t now;
                asm volatile("mov.u32 %0, %globaltimer_lo;" : "=r"(now));
                if (r >= 3 && ((lo < 380 && lo * 10 < hi * 8) || now - t_start > P.probe_deadline)) break;
            }
            side = best1 < best0;
            asm volatile("st.relaxed.gpu.global.u32 [%0], %1;" ::"l"(reinterpret_cast<uint32_t*>(box + BX_SIDE) + cta),
                         "r"(((epoch * 2 + 1) << 1) | side) : "memory");
        }
        side = __shfl_sync(0xffffffffu, side, 0);
        const uint32_t tag = epoch * 2 + 1;
        const uint32_t rcol = min(48 * (cta >> 3) + 8 * min(lane, 5u) + (cta & 7), D - 1u);
        const uint32_t rx = ldg16(p_x + rcol), rb2 = ldg16(P.b2 + rcol);
        const uint32_t rb1 = ldg16(p_b1 + cta * 32 + lane), rb1x = ldg16(p_b1 + 4096 + (cta & 31) * 16 + (lane & 15));
        __nv_bfloat16* const op = p_out + rcol;
        uint2* const x2_dst = reinterpret_cast<uint2*>(box + half_of(BX_X2 + ((lane >> 3) & 1) * 512, lane >> 1) + ((lane >> 2) & 1) * 128) +
                              (cta * 2 + (lane & 1));
        if (cta < NRED && lane < 16) st_msg8(x2_dst, 0u, 0u);
        mbar_wait(BAR(IT_K + 4));
        const uint4* part_src = box + (half_of(BX_PART + min(cta, NRED - 1u) * 512, side) + lane);
        float ga, gb;
        {
            const uint4 va = poll_msg<200>(box + BX_MOD + (2 * D + rcol) / 4, tag), vb = poll_msg<200>(box + BX_MOD + (5 * D + rcol) / 4, tag);
            const uint32_t ua = rcol & 2 ? va.y : va.x, ub = rcol & 2 ? vb.y : vb.x;
            ga = rcol & 1 ? bhi(ua) : blo(ua);
            gb = rcol & 1 ? bhi(ub) : blo(ub);
        }
        {
            const uint4* src = box + (half_of(BX_O + cta * 512, side) + lane);
            mbar_wait(BAR(IT_V + 7));
            uint4 v[4];
            poll_slots<4>(src, tag, v);
            float o0 = (__uint_as_float(v[0].x) + __uint_as_float(v[1].x)) + (__uint_as_float(v[2].x) + __uint_as_float(v[3].x));
            float o1 = (__uint_as_float(v[0].y) + __uint_as_float(v[1].y)) + (__uint_as_float(v[2].y) + __uint_as_float(v[3].y));
            const float o = (lane < 16 ? o0 : o1) + __shfl_xor_sync(0xffffffffu, lane < 16 ? o1 : o0, 16);
            sts16(sb + SM_O + lane * 2, f2b(o));
            asm volatile("bar.arrive 10, %0;" ::"n"(NCT + 32) : "memory");
            if (lane == 0) TS(21);
        }
        float r_x2 = 0.f;
        if (cta < NRED) {
            mbar_wait(BAR(IT_WO + 1));
            __nanosleep(200);
            const float sv = reduce_part(part_src, tag, lane TSPASS(23));
            r_x2 = rb(blo(rx) + rb(ga * rb(sv)));
            const uint32_t w = __float_as_uint(r_x2);
            const uint32_t w0 = __shfl_sync(0xffffffffu, w, lane & 1), w1 = __shfl_sync(0xffffffffu, w, (lane & 1) + 2),
                           w2 = __shfl_sync(0xffffffffu, w, (lane & 1) + 4);
            if (lane < 16) st_msg8(x2_dst, (w0 >> 16) | w1, (w2 >> 16) | (tag << 16));
            if (lane == 0) TS(11);
            __syncwarp();
            asm volatile("bar.arrive 9, 224;" ::: "memory");
        }
        {
            asm volatile("bar.sync 8, %0;" ::"n"(NCT + 32) : "memory");
            uint32_t hv[2];
#pragma unroll
            for (int k = 0; k < 2; k++) {
                const uint32_t ra = sb + SM_RED + (k ? 32 + (lane & 15) : lane) * 48;
                const float4 p0 = ldsf4(ra), p1 = ldsf4(ra + 16), p2 = ldsf4(ra + 32);
                const float r = ((p0.x + p0.y) + (p0.z + p0.w)) + ((p1.x + p1.y) + (p1.z + p1.w)) + ((p2.x + p2.y) + (p2.z + p2.w));
                const float u = rb(rb(r) + blo(k ? rb1x : rb1));
                const float z = 1.5957691216057308f * (u + 0.044715f * u * u * u);
                hv[k] = f2b(u * sigm(z));
            }
            sts16(sb + SM_O + lane * 2, hv[0]);
            if (lane < 16) sts16(sb + SM_O + 64 + lane * 2, hv[1]);
            __syncwarp();
            asm volatile("bar.arrive 6, %0;" ::"n"(NCT + 32) : "memory");
        }
        if (cta < NRED) {
            mbar_wait(BAR(IT_W2 + 1));
            __nanosleep(200);
            const float sv = reduce_part(part_src, tag + 1, lane TSPASS(24));
            const uint32_t y = f2b(r_x2 + rb(gb * rb(rb(sv) + blo(rb2))));
            if (lane < 6) asm volatile("st.global.u16 [%0], %1;" ::"l"(op), "r"(y) : "memory");
            if (cta == 0 && lane == 0) asm volatile("st.relaxed.gpu.global.u32 [%0], %1;" ::"l"(box + BX_EPOCH), "r"(epoch + 1) : "memory");
            if (lane == 0) TS(17);
        }
        return;
    }

    tid = __shfl_sync(0xffffffffu, tid, lane); cta = __shfl_sync(0xffffffffu, cta, 0);
    warp = tid >> 5; lane = tid & 31; grp = cta >> 3; rk = cta & 7;
    const uint32_t t = lane & 3, gq = lane >> 2;
    const uint32_t li = tid - 64;
    const bool is_ln = li < 192;
    const uint32_t lcol = is_ln ? 48 * (li >> 4) + 8 * (li & 1) + ((li >> 1) & 7) : 0;
    const uint32_t vi = warp * 24 + min(lane, 23u);
    uint32_t cv, epoch, x0, x1, x2;
    asm volatile("ld.global.nc.u32 %0, [%1];" : "=r"(cv) : "l"(reinterpret_cast<const uint32_t*>(p_c) + vi));
    asm volatile("ld.relaxed.gpu.global.u32 %0, [%1];" : "=r"(epoch) : "l"(box + BX_EPOCH) : "memory");
    x0 = ldg16(p_x + lcol); x1 = ldg16(p_x + lcol + 16); x2 = ldg16(p_x + lcol + 32);
    asm volatile("cp.async.commit_group;" ::: "memory");
    asm volatile("bar.sync 2, %0;" ::"n"(NTHREADS) : "memory");
    cp_arrive(BAR(IT_M));
    if (warp == 8) {
        const uint32_t idx = lane < 8 ? BX_MOD + cta * 8 + lane : lane < 16 ? BX_Q + cta * 8 + lane - 8 : BX_ML + cta * 2 + lane - 16;
        if (lane < 18 && (lane >= 8 || cta < NMOD)) st_msg(box + idx, 0u, 0u, 0u, 0u);
    }
    if (tid == 0) TS(20);
    uint32_t a[6];
    {
        PIN(cv);
        const float c0 = blo(cv), c1 = bhi(cv);
        const uint32_t av = pack2(c0 * sigm(c0), c1 * sigm(c1));
#pragma unroll
        for (int i = 0; i < 6; i++) a[i] = __shfl_sync(0xffffffffu, av, i * 4 + t);
    }
    const uint32_t scr_w = sb + SM_SMALL + (warp - 2) * 8;
    PIN(x0); PIN(x1); PIN(x2);
    if (is_ln) {
        const float3 xv = layernorm3(make_float3(blo(x0), blo(x1), blo(x2)), sb + SM_SMALL + 192, scr_w + 192, lane);
        sts16(sb + SM_XN + lcol * 2, __float_as_uint(xv.x) >> 16);
        sts16(sb + SM_XN + lcol * 2 + 32, __float_as_uint(xv.y) >> 16);
        sts16(sb + SM_XN + lcol * 2 + 64, __float_as_uint(xv.z) >> 16);
    }
    const uint32_t tag = epoch * 2 + 1, tag2 = epoch * 2 + 2;
    const uint32_t red_w = sb + SM_RED + warp * 160 + lane * 8, red_r = sb + SM_RED + min(tid, 39u) * 4;
    const uint32_t r4 = warp * 48 + lane, r2 = warp * 48 + 32 + (lane & 15);
    if (tid == 0) TS(1);

    asm volatile("cp.async.wait_group 0;" ::: "memory");
    asm volatile("fence.proxy.async.shared::cta;" ::: "memory");
    __syncwarp();
    if (tid == 0) TS(19);
    const bool extra = cta >= NRED;
    const uint32_t w1row = warp * 48 + (lane & 7) + 8 * (lane >> 4);
#pragma unroll 1
    for (uint32_t ph = cta < NMOD ? 0 : 1; ph < 2; ph++) {
        if (ph) {
            cbar();
            if (tid == 0) TS(2);
            const uint32_t l24 = min(lane, 23u), sl = (l24 >= 12 ? 132 : 0) + warp * 12 + l24;
            const uint4 v = poll_msg<150>(box + BX_MOD + sl, tag);
            sts64(sb + SM_MOD + sl * 8, v.x, v.y);
            __syncwarp();
            const uint32_t xn = lds32(sb + SM_XN + vi * 4), sa = lds32(sb + SM_MOD + vi * 4), ca = lds32(sb + SM_MOD + 1152 + vi * 4);
            const uint32_t one = pack2(1.f + blo(ca), 1.f + bhi(ca));
            const uint32_t pr = pack2(blo(xn) * blo(one), bhi(xn) * bhi(one));
            const uint32_t av = pack2(blo(pr) + blo(sa), bhi(pr) + bhi(sa));
#pragma unroll
            for (int i = 0; i < 6; i++) a[i] = __shfl_sync(0xffffffffu, av, i * 4 + t);
            if (tid == 0) TS(3);
            mbar_wait(BAR(IT_WQ + (warp >> 2)));
        }
        uint32_t b[4][6];
        strip_load<4>(sb + SM_M + ph * 36864 + r4 * 64, sb + SM_M + ph * 36864 + r2 * 64, (lane >> 1) & 3, b);
        const float r = strip_mma<4>(a, b, red_w, red_r, lane);
        if (warp == 0) {
            sts16(sb + SM_O + lane * 2, f2b(r));
            __syncwarp();
            if (lane < 8) st_msg(box + (ph ? BX_Q : BX_MOD) + cta * 8 + lane, lds32(sb + SM_O + lane * 8), lds32(sb + SM_O + lane * 8 + 4), 0u, tag);
        }
    }
    if (tid == 0) { mbar_arrive(BAR(BF_WQ)); TS(4); }
    if (li < 64) {
        const uint4 v = poll_msg(box + BX_Q + grp * 64 + li, tag);
        sts64(sb + SM_Q + li * 8, v.x, v.y);
    }
    cbar();
    if (tid == 0) TS(5);
    const uint32_t ob = sb + SM_O + t * 4;

    if (warp < 8) {
        uint32_t bq[4][2];
        const uint32_t msk = gq < 4 ? 0xffffffffu : 0u;
#pragma unroll
        for (int ks = 0; ks < 4; ks++) {
            const uint32_t qa = sb + SM_Q + ((gq & 1) * 64 + (gq & 2) * 16 + ks * 8 + t) * 4;
            bq[ks][0] = lds32(qa) & msk;
            bq[ks][1] = lds32(qa + 16) & msk;
        }
        float mx0 = -INFINITY, mx1 = -INFINITY;
        uint32_t rowaddr = sb + SM_K + (warp * 16 + (lane & 15)) * 128;
        const uint32_t xo = (lane >> 4) ^ (lane & 7);
        uint32_t sa = sb + SM_S + (warp * 8 + (lane >> 3)) * 4;
#pragma unroll 1
        for (int ch = 0; ch < 8; ch += 2) {
            uint32_t ka[2][4][4];
#pragma unroll
            for (int u = 0; u < 2; u++) {
                mbar_wait(BAR(IT_K + ch + u));
#pragma unroll
                for (int ks = 0; ks < 4; ks++) ldsm4(rowaddr + u * 16384 + (((2 * ks) ^ xo) << 4), ka[u][ks]);
            }
            float c[2][4];
#pragma unroll
            for (int u = 0; u < 2; u++) c[u][0] = c[u][1] = c[u][2] = c[u][3] = 0.f;
#pragma unroll
            for (int ks = 0; ks < 4; ks++)
#pragma unroll
                for (int u = 0; u < 2; u++)
                    mma16(c[u], ka[u][ks][0], ka[u][ks][1], ka[u][ks][2], ka[u][ks][3], bq[ks][0], bq[ks][1]);
            const float sc = 0.08838834764831845f;
#pragma unroll
            for (int u = 0; u < 2; u++) {
#pragma unroll
                for (int i = 0; i < 4; i++) c[u][i] = rb(rb(c[u][i] + __shfl_down_sync(0xffffffffu, c[u][i], 5)) * sc);
                if ((lane & 7) == 0) {
                    const uint32_t d = sa + u * 256;
                    stsf(d, c[u][0]); stsf(d + 2048, c[u][1]); stsf(d + 16, c[u][2]); stsf(d + 2064, c[u][3]);
                }
                mx0 = fmaxf(mx0, fmaxf(c[u][0], c[u][2]));
                mx1 = fmaxf(mx1, fmaxf(c[u][1], c[u][3]));
            }
            rowaddr += 32768; sa += 512;
        }
#pragma unroll
        for (int o = 8; o <= 16; o <<= 1) {
            mx0 = fmaxf(mx0, __shfl_xor_sync(0xffffffffu, mx0, o));
            mx1 = fmaxf(mx1, __shfl_xor_sync(0xffffffffu, mx1, o));
        }
        if (lane == 0) { stsf(sb + SM_SMALL + warp * 4, mx0); stsf(sb + SM_SMALL + 32 + warp * 4, mx1); }
        asm volatile("bar.sync 5, 256;" ::: "memory");
        if (tid == 0) { mbar_arrive(BAR(BF_K)); TS(6); }
        const uint32_t hd = warp >> 2;
        const float4 ma = ldsf4(sb + SM_SMALL + hd * 32), mb = ldsf4(sb + SM_SMALL + hd * 32 + 16);
        const float4 s4 = ldsf4(sb + SM_S + tid * 16);
        const float m = fmaxf(fmaxf(fmaxf(ma.x, ma.y), fmaxf(ma.z, ma.w)), fmaxf(fmaxf(mb.x, mb.y), fmaxf(mb.z, mb.w)));
        const float p0 = ex2((s4.x - m) * LOG2E), p1 = ex2((s4.y - m) * LOG2E), p2 = ex2((s4.z - m) * LOG2E), p3 = ex2((s4.w - m) * LOG2E);
        sts64(sb + SM_P + tid * 8, pack2(p0, p1), pack2(p2, p3));
        float l = (p0 + p1) + (p2 + p3);
#pragma unroll
        for (int o = 16; o > 0; o >>= 1) l += __shfl_xor_sync(0xffffffffu, l, o);
        if (lane == 0) { stsf(sb + SM_SMALL + 128 + warp * 4, l); stsf(sb + SM_SMALL + 160 + hd * 4, m); }
        asm volatile("bar.sync 5, 256;" ::: "memory");
        if (tid == 0) TS(7);
    }

    uint32_t wad[3];
#pragma unroll
    for (int i = 0; i < 3; i++) {
        const uint32_t T = warp * 3 + i, blk = T >> 2, ch = 2 * (T & 3) + ((lane >> 3) & 1);
        const uint32_t fr = ((lane & 7) + 8 * (lane >> 4)) * 9 + blk;
        wad[i] = sb + fr * 128 + ((ch ^ (fr & 7)) << 4);
        PIN(wad[i]);
    }
    if (warp < 4) {
        float c[2][4];
#pragma unroll
        for (int i = 0; i < 2; i++) c[i][0] = c[i][1] = c[i][2] = c[i][3] = 0.f;
        const uint32_t row = (lane & 7) + 8 * (lane >> 4);
        const uint32_t off = sb + SM_RING + row * 128 + (((2 * warp + ((lane >> 3) & 1)) ^ (lane & 7)) << 4);
        uint32_t pp = sb + SM_P + ((gq & 1) * 512 + t) * 2;
        const uint32_t mul = gq < 2 ? 1u : gq < 4 ? 65536u : 0u;
        float f0 = 0.f, f1 = 0.f;
        uint4* o_dst = box;
        uint32_t slot = 0;
#pragma unroll 1
        for (int ch = 0; ch < 8; ch++) {
            uint32_t bp[16];
#pragma unroll
            for (int i = 0; i < 16; i++) bp[i] = lds16(pp + i * 8) * mul;
            if (ch == 7) {
                asm volatile("bar.sync 3, %0;" ::"n"(NCT) : "memory");
                f0 = ldsf(sb + SM_SMALL + 176); f1 = ldsf(sb + SM_SMALL + 180);
                const uint32_t ro = grp * 8 + (t & 1) * 4 + warp;
                o_dst = box + (half_of(BX_O + ro * 512, lds32(sb + SM_XN + ro * 4)) + rk * 16 + gq);
            }
            uint32_t base = off + slot * 16384;
            PIN(base);
            mbar_wait(BAR(IT_V + ch));
            uint32_t va[8][4];
#pragma unroll
            for (int ks = 0; ks < 8; ks++) ldsm4t(base + ks * 2048, va[ks]);
#pragma unroll
            for (int ks = 0; ks < 8; ks++) mma16(c[ks & 1], va[ks][0], va[ks][1], va[ks][2], va[ks][3], bp[2 * ks], bp[2 * ks + 1]);
            if ((ch < 3 || ch == 4) && lane == 0) mbar_arrive(BAR(ch == 4 ? BF_X : BF_V0 + ch));
            slot = slot == 4 ? 0 : slot + 1;
            pp += 128;
        }
        if (t < 2) {
            st_msg(o_dst, __float_as_uint((c[0][0] + c[1][0]) * f0), __float_as_uint((c[0][1] + c[1][1]) * f1), 0u, tag);
            st_msg(o_dst + 8, __float_as_uint((c[0][2] + c[1][2]) * f0), __float_as_uint((c[0][3] + c[1][3]) * f1), 0u, tag);
        }
        if (tid == 0) TS(8);
    } else {
        if (warp == 4) {
            const uint32_t hd = lane & 1;
            const float m_own = ldsf(sb + SM_SMALL + 160 + hd * 4);
            const float4 l4 = ldsf4(sb + SM_SMALL + 128 + hd * 16);
            if (lane < 2) st_msg(box + BX_ML + cta * 2 + lane, __float_as_uint(m_own), __float_as_uint((l4.x + l4.y) + (l4.z + l4.w)), 0u, tag);
            const uint4 v = poll_msg(box + BX_ML + grp * 16 + (lane & 15), tag);
            const float ms = __uint_as_float(v.x);
            float M = ms;
#pragma unroll
            for (int o = 2; o <= 8; o <<= 1) M = fmaxf(M, __shfl_xor_sync(0xffffffffu, M, o));
            float L = __uint_as_float(v.y) * ex2((ms - M) * LOG2E);
#pragma unroll
            for (int o = 2; o <= 8; o <<= 1) L += __shfl_xor_sync(0xffffffffu, L, o);
            if (lane < 2) stsf(sb + SM_SMALL + 176 + lane * 4, ex2((m_own - M) * LOG2E) * rcp(L));
        } else if (warp >= 8) {
#pragma unroll 1
            for (uint32_t i = tid - 256; i < 288; i += 128) {
                const uint4 v = poll_msg<200>(box + BX_MOD + 432 + i, tag);
                sts64(sb + SM_MOD + i * 8, v.x, v.y);
            }
            mbar_wait(BAR(IT_V + 2));
            const uint32_t u = tid - 256;
            const uint32_t* side = reinterpret_cast<const uint32_t*>(box + BX_SIDE) + u;
            uint32_t sp;
            unsigned n = 0;
#pragma unroll 1
            do {
                if (n) __nanosleep(500);
                asm volatile("ld.relaxed.gpu.global.u32 %0, [%1];" : "=r"(sp) : "l"(side) : "memory");
            } while (__any_sync(0xffffffffu, (sp ^ (tag << 1)) > 1u) && ++n < SPIN_MAX);
            sts32(sb + SM_XN + u * 4, sp & 1);
            asm volatile("bar.sync 7, 128;" ::: "memory");
#pragma unroll
            for (int k = 0; k < 2; k++) {
                const uint32_t rp = k * 64 + (u >> 1);
                if (rp < NRED) st_msg(box + (half_of(BX_PART + rp * 512, lds32(sb + SM_XN + rp * 4)) + cta * 2 + (u & 1)), 0u, 0u, 0u, 0u);
            }
            const uint32_t ro = grp * 8 + (u >> 4);
            st_msg(box + (half_of(BX_O + ro * 512, lds32(sb + SM_XN + ro * 4)) + rk * 16 + (u & 15)), 0u, 0u, 0u, 0u);
            asm volatile("bar.arrive 3, %0;" ::"n"(NCT) : "memory");
            if (tid == 256) TS(18);
        }
        if (warp < 8) asm volatile("bar.sync 3, %0;" ::"n"(NCT) : "memory");
    }

    uint4* const part_dst = box + (half_of(BX_PART + (warp * 8 + gq) * 512, lds32(sb + SM_XN + (warp * 8 + gq) * 4)) + cta * 2 + (t & 1));
    const uint32_t my_side = lds32(sb + SM_XN + cta * 4);
    {
        uint32_t wa[3][8];
        mbar_wait(BAR(IT_WO));
#pragma unroll
        for (int i = 0; i < 3; i++) ldsm4t(wad[i] + SM_WO, &wa[i][0]);
        const bool pre0 = mbar_test(BAR(IT_WO + 1));
        if (pre0) {
#pragma unroll
            for (int i = 0; i < 3; i++) ldsm4t(wad[i] + SM_WO + 16 * 1152, &wa[i][4]);
        }
        asm volatile("bar.sync 10, %0;" ::"n"(NCT + 32) : "memory");
        if (tid == 0) TS(9);
        const uint32_t b0 = lds32(ob), b1 = lds32(ob + 16), b2 = lds32(ob + 32), b3 = lds32(ob + 48);
        float c[3][4];
#pragma unroll
        for (int i = 0; i < 3; i++) {
            c[i][0] = c[i][1] = c[i][2] = c[i][3] = 0.f;
            mma16(c[i], wa[i][0], wa[i][1], wa[i][2], wa[i][3], b0, b1);
        }
        if (!pre0) {
            mbar_wait(BAR(IT_WO + 1));
#pragma unroll
            for (int i = 0; i < 3; i++) ldsm4t(wad[i] + SM_WO + 16 * 1152, &wa[i][4]);
        }
#pragma unroll
        for (int i = 0; i < 3; i++) mma16(c[i], wa[i][4], wa[i][5], wa[i][6], wa[i][7], b2, b3);
        if (t < 2) st_msg(part_dst, __float_as_uint(t ? c[0][2] : c[0][0]), __float_as_uint(t ? c[1][2] : c[1][0]),
                          __float_as_uint(t ? c[2][2] : c[2][0]), tag);
        if (tid == 0) TS(10);
    }
    uint32_t wb[6][4], wx[3][4];
    const uint32_t w1bar = BAR((lane & 1) && extra ? IT_W1X : IT_W1 + (warp >> 2));
    const uint32_t w1a = sb + SM_W1 + w1row * 64 + ((((lane >> 3) & 1) ^ ((lane >> 1) & 3)) << 4);
    const uint32_t w1x = sb + SM_W1X + w1row * 32 + ((lane >> 3) & 1) * 16;
#define W1_LOAD() do { _Pragma("unroll") for (int k = 0; k < 3; k++) { \
        if (extra) ldsm4t(w1x + k * 512, wx[k]); \
        ldsm4t(w1a + k * 1024, wb[k * 2]); ldsm4t((w1a ^ 32) + k * 1024, wb[k * 2 + 1]); } } while (0)
    bool pre1 = false;
    if (is_ln) {
        const uint32_t ma = sb + SM_MOD + lcol * 2;
        float c0 = rb(1.f + blo(lds16(ma + 2 * D))), c1 = rb(1.f + blo(lds16(ma + 2 * D + 32))), c2 = rb(1.f + blo(lds16(ma + 2 * D + 64)));
        float s0 = blo(lds16(ma)), s1 = blo(lds16(ma + 32)), s2 = blo(lds16(ma + 64));
        const uint2* src = reinterpret_cast<const uint2*>(box + half_of(BX_X2 + (cta & 2) * 256, my_side) + (cta & 1) * 128) + li;
        const uint32_t yd = sb + SM_VEC + lcol * 2;
        uint2 v;
        unsigned n = 0;
        if (cta < NRED) asm volatile("bar.sync 9, 224;" ::: "memory");
        else mbar_wait(w1bar);
        pre1 = mbar_test(w1bar);
        if (pre1) W1_LOAD();
#pragma unroll 1
        do { v = ld_msg8(src); } while (__any_sync(0xffffffffu, (v.y >> 16) != (tag & 0xffffu)) && ++n < SPIN_MAX);
        if (tid == 64) TS(12);
        float3 y = layernorm3(make_float3(blo(v.x), bhi(v.x), blo(v.y)), sb + SM_SMALL, scr_w, lane);
        y = layernorm3(make_float3(rb(rb(y.x * c0) + s0), rb(rb(y.y * c1) + s1), rb(rb(y.z * c2) + s2)), sb + SM_SMALL + 64, scr_w + 64, lane);
        sts16(yd, __float_as_uint(y.x) >> 16); sts16(yd + 32, __float_as_uint(y.y) >> 16); sts16(yd + 64, __float_as_uint(y.z) >> 16);
        if (tid == 64) TS(22);
    }
    {
        const uint32_t ya = sb + SM_VEC + (warp * 24 + t) * 4;
        const uint32_t rd = sb + SM_RED + (t * 16 + gq) * 48 + warp * 4;
        if (!pre1) {
            mbar_wait(w1bar);
            __syncwarp();
            W1_LOAD();
        }
        cbar();
        if (tid == 0) TS(13);
#pragma unroll
        for (int i = 0; i < 6; i++) a[i] = lds32(ya + i * 16);
        float c[3][4];
#pragma unroll
        for (int j = 0; j < 3; j++) c[j][0] = c[j][1] = c[j][2] = c[j][3] = 0.f;
#pragma unroll
        for (int k = 0; k < 3; k++) {
#pragma unroll
            for (int j = 0; j < 2; j++) mma16(c[j], wb[k * 2 + j][0], wb[k * 2 + j][1], wb[k * 2 + j][2], wb[k * 2 + j][3], a[2 * k], a[2 * k + 1]);
            if (extra) mma16(c[2], wx[k][0], wx[k][1], wx[k][2], wx[k][3], a[2 * k], a[2 * k + 1]);
        }
        if (t < 3) {
            stsf(rd, t == 0 ? c[0][0] : t == 1 ? c[1][0] : c[2][0]);
            stsf(rd + 8 * 48, t == 0 ? c[0][2] : t == 1 ? c[1][2] : c[2][2]);
        }
        asm volatile("bar.arrive 8, %0;" ::"n"(NCT + 32) : "memory");
    }
    {
        uint32_t wa[3][12];
        mbar_wait(BAR((lane & 1) && extra ? IT_W2C : IT_W2));
        __syncwarp();
#pragma unroll
        for (int i = 0; i < 3; i++) {
            ldsm4t(wad[i] + SM_W2, &wa[i][0]);
            if (extra) ldsm4t(wad[i] + SM_W2 + 32 * 1152, &wa[i][8]);
        }
        const bool pre = mbar_test(BAR(IT_W2 + 1));
        if (pre) {
#pragma unroll
            for (int i = 0; i < 3; i++) ldsm4t(wad[i] + SM_W2 + 16 * 1152, &wa[i][4]);
        }
        asm volatile("bar.sync 6, %0;" ::"n"(NCT + 32) : "memory");
        if (tid == 0) TS(14);
        uint32_t b[6];
#pragma unroll
        for (int i = 0; i < 6; i++) b[i] = lds32(ob + i * 16);
        float c[3][4], e[3][4], f[3][4];
#pragma unroll
        for (int i = 0; i < 3; i++) {
#pragma unroll
            for (int j = 0; j < 4; j++) c[i][j] = e[i][j] = f[i][j] = 0.f;
            mma16(c[i], wa[i][0], wa[i][1], wa[i][2], wa[i][3], b[0], b[1]);
            if (extra) mma16(e[i], wa[i][8], wa[i][9], wa[i][10], wa[i][11], b[4], b[5]);
        }
        if (!pre) {
            mbar_wait(BAR(IT_W2 + 1));
#pragma unroll
            for (int i = 0; i < 3; i++) ldsm4t(wad[i] + SM_W2 + 16 * 1152, &wa[i][4]);
        }
        if (tid == 0) TS(15);
#pragma unroll
        for (int i = 0; i < 3; i++) mma16(f[i], wa[i][4], wa[i][5], wa[i][6], wa[i][7], b[2], b[3]);
        float r[3];
#pragma unroll
        for (int i = 0; i < 3; i++) r[i] = t ? (c[i][2] + e[i][2]) + f[i][2] : (c[i][0] + e[i][0]) + f[i][0];
        if (t < 2) st_msg(part_dst, __float_as_uint(r[0]), __float_as_uint(r[1]), __float_as_uint(r[2]), tag2);
        if (tid == 0) TS(16);
    }
#undef BAR
}

typedef CUresult (*EncodeFn)(CUtensorMap*, CUtensorMapDataType, cuuint32_t, void*, const cuuint64_t*, const cuuint64_t*,
                             const cuuint32_t*, const cuuint32_t*, CUtensorMapInterleave, CUtensorMapSwizzle,
                             CUtensorMapL2promotion, CUtensorMapFloatOOBfill);

void make_map(EncodeFn enc, CUtensorMap* m, const void* base, uint64_t cols, uint64_t rows, uint32_t bc, uint32_t br,
              CUtensorMapSwizzle sw, CUtensorMapL2promotion promo) {
    cuuint64_t dims[2] = {cols, rows};
    cuuint64_t strides[1] = {cols * 2};
    cuuint32_t box[2] = {bc, br};
    cuuint32_t es[2] = {1, 1};
    enc(m, CU_TENSOR_MAP_DATA_TYPE_BFLOAT16, 2, const_cast<void*>(base), dims, strides, box, es,
        CU_TENSOR_MAP_INTERLEAVE_NONE, sw, promo, CU_TENSOR_MAP_FLOAT_OOB_FILL_NONE);
}

struct Tune { int t0, rate, stagger, gap, rate2, win, win2, pf_m, mw; char order[40], stag[40]; };
Tune g_tune = {-1430, 2450, 670, 150, 2550, 70, 70, 0, 20, "abcKKKKKKKKVVVVVVVVOOxdefXYX", "8888888888888888888448888888"};
void make_schedule(Params& P, double speed) {
    const Tune& T = g_tune;
    int nk = 0, nv = 0, no = 0, nx = 0, n = 0, hist[40], hb[40], nh = 0;
    bool after = false;
    const double stagger = T.stagger / speed;
    double t = T.t0 + (T.stagger - stagger) / 2 + 31104 * 100.0 / (T.rate * speed);
    hb[nh] = T.mw * 1024; hist[nh++] = IT_M;
    for (const char* c = T.order; *c && n < NPOS; c++) {
        int item, bytes;
        switch (*c) {
            case 'a': case 'b': case 'c': item = IT_WQ + (*c - 'a'); bytes = 12288; break;
            case 'K': item = IT_K + nk++; bytes = 16384; break;
            case 'V': item = IT_V + nv++; bytes = 16384; break;
            case 'O': item = IT_WO + no++; bytes = 18432; break;
            case 'd': case 'e': case 'f': item = IT_W1 + (*c - 'd'); bytes = 12288; break;
            case 'X': item = IT_W2 + nx++; bytes = 18432; break;
            case 'x': item = IT_W1X; bytes = 4608; break;
            default: item = IT_W2C; bytes = 4608; break;
        }
        t += bytes * 100.0 / ((after ? T.rate2 : T.rate) * speed);
        int j = nh - 1, sum = bytes;
        while (j >= 0 && sum + hb[j] <= (after ? T.win2 : T.win) * 1024) sum += hb[j--];
        const int gate = j >= 0 ? hist[j] : IT_NONE;
        const int sg = T.stag[n] - '0';
        int tt = (int)(t + (8 - sg) * stagger / 16.0);
        tt = tt < 0 ? 0 : tt > 65535 ? 65535 : tt;
        P.sched[n++] = (uint32_t)item | (gate << 6) | (sg << 12) | ((uint32_t)tt << 16);
        if (bytes > 8192) { hb[nh] = bytes; hist[nh++] = item; }
        if (no == 2 && nv == 8 && !after) { after = true; t += T.gap; }
    }
    P.stagger = (uint32_t)stagger;
    P.probe_deadline = (uint32_t)(9300 / speed);
}

__device__ float f_a[FF], f_mod[6 * D], f_q[4096], f_x2[D], f_t[FF];
typedef const __nv_bfloat16* CB;
__device__ __forceinline__ float bf(CB p, size_t i) { return __bfloat162float(p[i]); }
__global__ void fb_gemv(const float* v, CB w, int K, int N, float* out) {
    const int n = blockIdx.x * blockDim.x + threadIdx.x;
    if (n >= N) return;
    float s = 0.f;
    for (int k = 0; k < K; k++) s += v[k] * bf(w, (size_t)k * N + n);
    out[n] = rb(s);
}
__device__ float fb_ln(float v, float* sh) {
    __syncthreads(); sh[threadIdx.x] = v; __syncthreads();
    float s = 0.f, q = 0.f;
    for (int i = 0; i < D; i++) s += sh[i];
    s /= D;
    for (int i = 0; i < D; i++) q += (sh[i] - s) * (sh[i] - s);
    return rb(rb(v - rb(s)) / rb(sqrtf(rb(rb(q / D) + 1e-5f))));
}
__global__ void fb_elem(int stage, CB x, CB c, CB b1, CB b2, __nv_bfloat16* out) {
    __shared__ float sh[D];
    const int i = threadIdx.x;
    if (stage == 0) { const float v = bf(c, i); f_a[i] = rb(v / (1.f + expf(-v))); }
    if (stage == 1) f_a[i] = rb(rb(fb_ln(bf(x, i), sh) * rb(1.f + f_mod[D + i])) + f_mod[i]);
    if (stage == 2) {
        f_x2[i] = rb(bf(x, i) + rb(f_mod[2 * D + i] * f_t[i]));
        f_a[i] = fb_ln(rb(rb(fb_ln(f_x2[i], sh) * rb(1.f + f_mod[4 * D + i])) + f_mod[3 * D + i]), sh);
    }
    if (stage == 3)
        for (int j = i; j < FF; j += D) {
            const float u = rb(f_t[j] + bf(b1, j));
            f_a[j] = rb(0.5f * u * (1.f + tanhf(0.7978845608028654f * (u + 0.044715f * u * u * u))));
        }
    if (stage == 4) out[i] = __float2bfloat16_rn(f_x2[i] + rb(f_mod[5 * D + i] * rb(f_t[i] + bf(b2, i))));
}
__global__ void fb_attn(CB k, CB v) {
    __shared__ float p[WIN], red[128];
    const int h = blockIdx.x, t = threadIdx.x;
    const size_t base = ((size_t)(h / 2) * SK + SK - WIN) * 128;
    float m = -INFINITY, l = 0.f, o = 0.f;
    for (int j = t; j < WIN; j += 128) {
        float s = 0.f;
        for (int d = 0; d < 128; d++) s += f_q[h * 128 + d] * bf(k, base + (size_t)j * 128 + d);
        p[j] = rb(rb(s) * 0.08838834764831845f);
        m = fmaxf(m, p[j]);
    }
    red[t] = m; __syncthreads();
    for (int i = 0; i < 128; i++) m = fmaxf(m, red[i]);
    __syncthreads();
    for (int j = t; j < WIN; j += 128) { p[j] = expf(p[j] - m); l += p[j]; }
    red[t] = l; __syncthreads();
    l = 0.f;
    for (int i = 0; i < 128; i++) l += red[i];
    for (int j = 0; j < WIN; j++) o += rb(p[j] / l) * bf(v, base + (size_t)j * 128 + t);
    f_a[h * 128 + t] = rb(o);
}
void fallback(void* const* in, void* out) {
    float *a, *mod, *q, *t;
    cudaGetSymbolAddress((void**)&a, f_a); cudaGetSymbolAddress((void**)&mod, f_mod);
    cudaGetSymbolAddress((void**)&q, f_q); cudaGetSymbolAddress((void**)&t, f_t);
#define ELEM(s) fb_elem<<<1, D>>>(s, (CB)in[0], (CB)in[10], (CB)in[7], (CB)in[9], (__nv_bfloat16*)out)
    ELEM(0); fb_gemv<<<54, 64>>>(a, (CB)in[11], D, 6 * D, mod);
    ELEM(1); fb_gemv<<<64, 64>>>(a, (CB)in[3], D, 4096, q);
    fb_attn<<<32, 128>>>((CB)in[1], (CB)in[2]); fb_gemv<<<9, 64>>>(a, (CB)in[4], 4096, D, t);
    ELEM(2); fb_gemv<<<72, 64>>>(a, (CB)in[6], D, FF, t);
    ELEM(3); fb_gemv<<<9, 64>>>(a, (CB)in[8], FF, D, t);
    ELEM(4);
#undef ELEM
}

}

extern "C" void kernel_launch(void* const* d_in, const int* in_sizes, int n_in, void* d_out, int out_size) {
    (void)in_sizes; (void)n_in; (void)out_size;
    int dev = 0, sms = 0, occ = 0, mclk = 0, bus = 0;
    cudaGetDevice(&dev);
    cudaDeviceGetAttribute(&sms, cudaDevAttrMultiProcessorCount, dev);
    cudaDeviceGetAttribute(&mclk, cudaDevAttrMemoryClockRate, dev);
    cudaDeviceGetAttribute(&bus, cudaDevAttrGlobalMemoryBusWidth, dev);
    cudaFuncSetAttribute(fused_kernel, cudaFuncAttributeMaxDynamicSharedMemorySize, SM_TOTAL);
    cudaOccupancyMaxActiveBlocksPerMultiprocessor(&occ, fused_kernel, NTHREADS, SM_TOTAL);
    void* fn = nullptr;
    cudaDriverEntryPointQueryResult qr;
    cudaGetDriverEntryPoint("cuTensorMapEncodeTiled", &fn, cudaEnableDefault, &qr);
    if (sms * occ < NCTA || !fn) { (void)cudaGetLastError(); fallback(d_in, d_out); return; }
    EncodeFn enc = (EncodeFn)fn;

    Params P;
    make_map(enc, &P.m_wq, d_in[3], 4096, D, 32, 192, CU_TENSOR_MAP_SWIZZLE_64B, CU_TENSOR_MAP_L2_PROMOTION_L2_128B);
    make_map(enc, &P.m_k, d_in[1], 64, (uint64_t)HKV * SK * 2, 64, 128, CU_TENSOR_MAP_SWIZZLE_128B, CU_TENSOR_MAP_L2_PROMOTION_L2_256B);
    make_map(enc, &P.m_v, d_in[2], 64, (uint64_t)HKV * SK * 2, 64, 128, CU_TENSOR_MAP_SWIZZLE_128B, CU_TENSOR_MAP_L2_PROMOTION_L2_256B);
    make_map(enc, &P.m_wo, d_in[4], 64, 4096 * 9, 64, 144, CU_TENSOR_MAP_SWIZZLE_128B, CU_TENSOR_MAP_L2_PROMOTION_L2_256B);
    make_map(enc, &P.m_w1, d_in[6], FF, D, 32, 192, CU_TENSOR_MAP_SWIZZLE_64B, CU_TENSOR_MAP_L2_PROMOTION_L2_128B);
    make_map(enc, &P.m_w1x, d_in[6], FF, D, 16, 192, CU_TENSOR_MAP_SWIZZLE_NONE, CU_TENSOR_MAP_L2_PROMOTION_L2_64B);
    make_map(enc, &P.m_w2, d_in[8], 64, FF * 9, 64, 144, CU_TENSOR_MAP_SWIZZLE_128B, CU_TENSOR_MAP_L2_PROMOTION_L2_256B);
    P.b2 = (const __nv_bfloat16*)d_in[9];
    const double speed = mclk > 0 && bus > 0 ? (double)mclk * bus / (2619000.0 * 5120.0) : 1.0;
    make_schedule(P, speed);
    void* boxp = nullptr;
    cudaGetSymbolAddress(&boxp, g_box);
    uint4* box = (uint4*)(((uintptr_t)boxp + (2 << 20) - 1) & ~(uintptr_t)((2 << 20) - 1));
    fused_kernel<<<NCTA, NTHREADS, SM_TOTAL>>>((const __nv_bfloat16*)d_in[11], (const __nv_bfloat16*)d_in[10], (const __nv_bfloat16*)d_in[0],
                                               box, (const __nv_bfloat16*)d_in[7], (__nv_bfloat16*)d_out, P);
}
```

```cpp
#include <cuda_runtime.h>
#include <cuda_bf16.h>
#include <cuda.h>
#include <stdint.h>

namespace {

constexpr int D = 576, HKV = 16, SK = 32768, WIN = 4096, FF = 4608;
constexpr int NATT = 128;
constexpr int NRED = 96;
constexpr int NMOD = 108;
constexpr int NCW = 12;
constexpr int NCT = NCW * 32;
constexpr int NTHREADS = NCT + 64;

constexpr int SM_K = 0;
constexpr int SM_WO = 0;
constexpr int SM_W2 = 36864;
constexpr int SM_W1 = 92160;
constexpr int SM_RING = 131072;
constexpr int SM_W1X = SM_RING + 3 * 16384;
constexpr int SM_M = SM_RING;
constexpr int SM_WQ = SM_RING + 36864;
constexpr int SM_MISC = SM_RING + 5 * 16384;
constexpr int SM_MOD = SM_MISC;
constexpr int SM_VEC = SM_MOD + 2304;
constexpr int SM_XN = SM_VEC + 1152;
constexpr int SM_Q = SM_XN + 1152;
constexpr int SM_S = SM_Q + 512;
constexpr int SM_P = SM_S + 4096;
constexpr int SM_RED = SM_P + 2048;
constexpr int SM_SMALL = SM_RED + 2304;
constexpr int SM_O = SM_SMALL + 256;
constexpr int SM_BAR = SM_O + 128;
constexpr int SM_TOTAL = SM_BAR + 40 * 8;
static_assert(SM_TOTAL <= 232448, "smem");

enum { IT_M = 0, IT_WQ = 1, IT_K = 4, IT_V = 12, IT_WO = 20, IT_W2 = 22, IT_W1 = 24, IT_W2C = 27, IT_W1X = 28,
       BF_WQ = 29, BF_K = 30, BF_X = 31, BF_V0 = 32  , NBAR_USED = 35, NPOS = 28, IT_NONE = 63 };

enum { BX_X2 = 0,
       BX_O = 1024,
       BX_PART = BX_O + NATT * 512,
       BX_MOD = BX_PART + NRED * 512,
       BX_Q = BX_MOD + 864,
       BX_ML = BX_Q + NATT * 8,
       BX_SIDE = BX_ML + NATT * 2,
       BX_EPOCH = BX_SIDE + 32,
       BX_TOTAL = BX_EPOCH + 8 };
static_assert(BX_TOTAL * 16 <= (2 << 20), "mailboxes stay inside one 2 MB page");
__device__ uint4 g_box[(4 << 20) / 16];
__device__ __forceinline__ uint32_t half_of(uint32_t pair, uint32_t side) {
    constexpr uint32_t MASK = ((1u << 13) | (1u << 16) | (1u << 17) | (1u << 19)) >> 4;
    return pair + (((__popc(pair & MASK) ^ side) & 1u) << 8);
}

constexpr unsigned SPIN_MAX = 1u << 21;
#define PIN(x) asm volatile("" : "+r"(x))

__device__ __forceinline__ uint32_t smem_u32(const void* p) { return (uint32_t)__cvta_generic_to_shared(p); }
__device__ __forceinline__ void mbar_init(uint32_t bar, uint32_t cnt) {
    asm volatile("mbarrier.init.shared::cta.b64 [%0], %1;" ::"r"(bar), "r"(cnt) : "memory");
}
__device__ __forceinline__ void mbar_expect_tx(uint32_t bar, uint32_t bytes) {
    asm volatile("mbarrier.arrive.expect_tx.shared::cta.b64 _, [%0], %1;" ::"r"(bar), "r"(bytes) : "memory");
}
__device__ __forceinline__ void mbar_arrive(uint32_t bar) {
    asm volatile("mbarrier.arrive.shared::cta.b64 _, [%0];" ::"r"(bar) : "memory");
}
__device__ __forceinline__ void mbar_wait(uint32_t bar) {
    uint32_t ok;
    unsigned n = 0;
#pragma unroll 1
    do {
        asm volatile("{\n.reg .pred p;\nmbarrier.try_wait.parity.shared::cta.b64 p, [%1], 0;\nselp.u32 %0, 1, 0, p;\n}"
                     : "=r"(ok) : "r"(bar) : "memory");
    } while (!ok && ++n < SPIN_MAX);
}
__device__ __forceinline__ bool mbar_test(uint32_t bar) {
    uint32_t ok;
    asm volatile("{\n.reg .pred p;\nmbarrier.test_wait.parity.shared::cta.b64 p, [%1], 0;\nselp.u32 %0, 1, 0, p;\n}"
                 : "=r"(ok) : "r"(bar) : "memory");
    return __all_sync(0xffffffffu, ok);
}
__device__ __forceinline__ void tma2d(uint32_t dst, const CUtensorMap* map, int c0, int c1, uint32_t bar, uint64_t pol) {
    asm volatile("cp.async.bulk.tensor.2d.shared::cluster.global.mbarrier::complete_tx::bytes.L2::cache_hint [%0], [%1, {%3, %4}], [%2], %5;"
                 ::"r"(dst), "l"(map), "r"(bar), "r"(c0), "r"(c1), "l"(pol) : "memory");
}
__device__ __forceinline__ void cp16(uint32_t dst, const void* src) {
    asm volatile("cp.async.cg.shared.global.L2::128B [%0], [%1], 16;" ::"r"(dst), "l"(src) : "memory");
}
__device__ __forceinline__ void cp_arrive(uint32_t bar) {
    asm volatile("cp.async.mbarrier.arrive.noinc.shared::cta.b64 [%0];" ::"r"(bar) : "memory");
}
__device__ __forceinline__ void cbar() { asm volatile("bar.sync 1, %0;" ::"n"(NCT) : "memory"); }

__device__ __forceinline__ uint32_t lds32(uint32_t a) { uint32_t v; asm volatile("ld.shared.u32 %0, [%1];" : "=r"(v) : "r"(a) : "memory"); return v; }
__device__ __forceinline__ uint32_t lds16(uint32_t a) { uint32_t v; asm volatile("ld.shared.u16 %0, [%1];" : "=r"(v) : "r"(a) : "memory"); return v; }
__device__ __forceinline__ float ldsf(uint32_t a) { float v; asm volatile("ld.shared.f32 %0, [%1];" : "=f"(v) : "r"(a) : "memory"); return v; }
__device__ __forceinline__ float4 ldsf4(uint32_t a) {
    float4 v;
    asm volatile("ld.shared.v4.f32 {%0,%1,%2,%3}, [%4];" : "=f"(v.x), "=f"(v.y), "=f"(v.z), "=f"(v.w) : "r"(a) : "memory");
    return v;
}
__device__ __forceinline__ void sts32(uint32_t a, uint32_t v) { asm volatile("st.shared.u32 [%0], %1;" ::"r"(a), "r"(v) : "memory"); }
__device__ __forceinline__ void sts16(uint32_t a, uint32_t v) { asm volatile("st.shared.u16 [%0], %1;" ::"r"(a), "r"(v) : "memory"); }
__device__ __forceinline__ void stsf(uint32_t a, float v) { asm volatile("st.shared.f32 [%0], %1;" ::"r"(a), "f"(v) : "memory"); }
__device__ __forceinline__ void sts64(uint32_t a, uint32_t x, uint32_t y) { asm volatile("st.shared.v2.u32 [%0], {%1,%2};" ::"r"(a), "r"(x), "r"(y) : "memory"); }

__device__ __forceinline__ void st_msg(uint4* p, uint32_t a, uint32_t b, uint32_t c, uint32_t d) {
    asm volatile("{\n.reg .b128 t;\n.reg .b64 lo, hi;\nmov.b64 lo, {%1, %2};\nmov.b64 hi, {%3, %4};\nmov.b128 t, {lo, hi};\n"
                 "st.relaxed.gpu.global.b128 [%0], t;\n}" ::"l"(p), "r"(a), "r"(b), "r"(c), "r"(d) : "memory");
}
__device__ __forceinline__ uint4 ld_msg(const uint4* p) {
    uint4 v;
    asm volatile("{\n.reg .b128 t;\n.reg .b64 lo, hi;\nld.relaxed.gpu.global.b128 t, [%4];\nmov.b128 {lo, hi}, t;\n"
                 "mov.b64 {%0, %1}, lo;\nmov.b64 {%2, %3}, hi;\n}" : "=r"(v.x), "=r"(v.y), "=r"(v.z), "=r"(v.w) : "l"(p) : "memory");
    return v;
}
template <int BACKOFF = 0>
__device__ __forceinline__ uint4 poll_msg(const uint4* p, uint32_t tag) {
    uint4 v;
    v.w = tag + 1;
    unsigned n = 0;
#pragma unroll 1
    do {
        if (BACKOFF && n) __nanosleep(BACKOFF);
        if (v.w != tag) v = ld_msg(p);
    } while (__any_sync(0xffffffffu, v.w != tag) && ++n < SPIN_MAX);
    return v;
}
__device__ __forceinline__ void st_msg8(uint2* p, uint32_t a, uint32_t b) {
    asm volatile("{\n.reg .b64 t;\nmov.b64 t, {%1, %2};\nst.relaxed.gpu.global.b64 [%0], t;\n}" ::"l"(p), "r"(a), "r"(b) : "memory");
}
__device__ __forceinline__ uint2 ld_msg8(const uint2* p) {
    uint2 v;
    asm volatile("{\n.reg .b64 t;\nld.relaxed.gpu.global.b64 t, [%2];\nmov.b64 {%0, %1}, t;\n}" : "=r"(v.x), "=r"(v.y) : "l"(p) : "memory");
    return v;
}
__device__ __forceinline__ uint32_t ldg16(const __nv_bfloat16* p) {
    uint32_t v;
    asm volatile("ld.global.nc.u16 %0, [%1];" : "=r"(v) : "l"(p));
    return v;
}

__device__ __forceinline__ void ldsm4(uint32_t a, uint32_t* r) {
    asm volatile("ldmatrix.sync.aligned.m8n8.x4.shared.b16 {%0,%1,%2,%3}, [%4];" : "=r"(r[0]), "=r"(r[1]), "=r"(r[2]), "=r"(r[3]) : "r"(a) : "memory");
}
__device__ __forceinline__ void ldsm4t(uint32_t a, uint32_t* r) {
    asm volatile("ldmatrix.sync.aligned.m8n8.x4.trans.shared.b16 {%0,%1,%2,%3}, [%4];" : "=r"(r[0]), "=r"(r[1]), "=r"(r[2]), "=r"(r[3]) : "r"(a) : "memory");
}
__device__ __forceinline__ void ldsm2t(uint32_t a, uint32_t* r) {
    asm volatile("ldmatrix.sync.aligned.m8n8.x2.trans.shared.b16 {%0,%1}, [%2];" : "=r"(r[0]), "=r"(r[1]) : "r"(a) : "memory");
}
__device__ __forceinline__ void mma16(float* c, uint32_t a0, uint32_t a1, uint32_t a2, uint32_t a3, uint32_t b0, uint32_t b1) {
    asm volatile("mma.sync.aligned.m16n8k16.row.col.f32.bf16.bf16.f32 {%0,%1,%2,%3}, {%4,%5,%6,%7}, {%8,%9}, {%0,%1,%2,%3};"
                 : "+f"(c[0]), "+f"(c[1]), "+f"(c[2]), "+f"(c[3]) : "r"(a0), "r"(a1), "r"(a2), "r"(a3), "r"(b0), "r"(b1));
}

__device__ __forceinline__ uint32_t pack2(float lo, float hi) {
    uint32_t r;
    asm("cvt.rn.bf16x2.f32 %0, %1, %2;" : "=r"(r) : "f"(hi), "f"(lo));
    return r;
}
__device__ __forceinline__ float rb(float x) { return __uint_as_float(pack2(0.f, x)); }
__device__ __forceinline__ uint32_t f2b(float x) { return pack2(x, 0.f); }
__device__ __forceinline__ float blo(uint32_t u) { return __uint_as_float(u << 16); }
__device__ __forceinline__ float bhi(uint32_t u) { return __uint_as_float(u & 0xffff0000u); }
__device__ __forceinline__ float ex2(float x) { float r; asm("ex2.approx.ftz.f32 %0, %1;" : "=f"(r) : "f"(x)); return r; }
__device__ __forceinline__ float rcp(float x) { float r; asm("rcp.approx.ftz.f32 %0, %1;" : "=f"(r) : "f"(x)); return r; }
constexpr float LOG2E = 1.4426950408889634f;
__device__ __forceinline__ float sigm(float x) { return rcp(1.f + ex2(-LOG2E * x)); }

__device__ __forceinline__ float3 layernorm3(float3 v, uint32_t scr, uint32_t scr_w, int lane) {
    float s = v.x + v.y + v.z, q = v.x * v.x + v.y * v.y + v.z * v.z;
#pragma unroll
    for (int o = 16; o > 0; o >>= 1) {
        s += __shfl_xor_sync(0xffffffffu, s, o);
        q += __shfl_xor_sync(0xffffffffu, q, o);
    }
    if (lane == 0) sts64(scr_w, __float_as_uint(s), __float_as_uint(q));
    asm volatile("bar.sync 4, 192;" ::: "memory");
    const float4 e0 = ldsf4(scr), e1 = ldsf4(scr + 16), e2 = ldsf4(scr + 32);
    const float mean = ((e0.x + e0.z) + (e1.x + e1.z) + (e2.x + e2.z)) * (1.0f / D);
    const float var = ((e0.y + e0.w) + (e1.y + e1.w) + (e2.y + e2.w)) * (1.0f / D) - mean * mean;
    const float mb = rb(mean);
    float den;
    asm("sqrt.approx.ftz.f32 %0, %1;" : "=f"(den) : "f"(rb(rb(fmaxf(var, 0.f)) + 1e-5f)));
    const float inv = rcp(rb(den));
    return make_float3(rb(rb(v.x - mb) * inv), rb(rb(v.y - mb) * inv), rb(rb(v.z - mb) * inv));
}

template <int NT>
__device__ __forceinline__ void strip_load(uint32_t p4, uint32_t p2, int x, uint32_t (&b)[NT][6]) {
#pragma unroll
    for (int n = 0; n < NT; n++) {
        ldsm4t(p4 + ((n ^ x) << 4), &b[n][0]);
        ldsm2t(p2 + ((n ^ x) << 4), &b[n][4]);
    }
}
__device__ __forceinline__ float red_sum(uint32_t red_r) {
    cbar();
    float v[NCW];
#pragma unroll
    for (int w = 0; w < NCW; w++) v[w] = ldsf(red_r + w * 160);
    return ((v[0] + v[1]) + (v[2] + v[3])) + ((v[4] + v[5]) + (v[6] + v[7])) + ((v[8] + v[9]) + (v[10] + v[11]));
}
template <int NT>
__device__ __forceinline__ void strip_mma_store(const uint32_t (&a)[6], const uint32_t (&b)[NT][6], uint32_t red_w, int lane) {
    float c[NT][4];
#pragma unroll
    for (int n = 0; n < NT; n++) c[n][0] = c[n][1] = c[n][2] = c[n][3] = 0.f;
#pragma unroll
    for (int k = 0; k < 3; k++)
#pragma unroll
        for (int n = 0; n < NT; n++) mma16(c[n], a[2 * k], a[2 * k], a[2 * k + 1], a[2 * k + 1], b[n][2 * k], b[n][2 * k + 1]);
    if (lane < 4) {
#pragma unroll
        for (int n = 0; n < NT; n++) sts64(red_w + n * 32, __float_as_uint(c[n][0]), __float_as_uint(c[n][1]));
    }
}
template <int NT>
__device__ __forceinline__ float strip_mma(const uint32_t (&a)[6], const uint32_t (&b)[NT][6], uint32_t red_w, uint32_t red_r, int lane) {
    strip_mma_store<NT>(a, b, red_w, lane);
    return red_sum(red_r);
}

template <int N>
__device__ __forceinline__ void poll_slots(const uint4* p, uint32_t tag, uint4 (&v)[N]) {
    uint32_t pend = (1u << N) - 1;
    unsigned n = 0;
    bool more;
#pragma unroll 1
    do {
#pragma unroll
        for (int i = 0; i < N; i++) if (pend & (1u << i)) v[i] = ld_msg(p + i * 32);
        uint32_t x = 0;
#pragma unroll
        for (int i = 0; i < N; i++) x |= v[i].w ^ tag;
        more = __any_sync(0xffffffffu, x != 0);
        if (!more) break;
        pend = 0;
#pragma unroll
        for (int i = 0; i < N; i++) pend |= v[i].w != tag ? 1u << i : 0u;
    } while (++n < SPIN_MAX);
}
__device__ __forceinline__ float reduce_part(const uint4* p, uint32_t tag, int lane) {
    uint4 v[8];
    poll_slots<8>(p, tag, v);
#define F(i, c) __uint_as_float(v[i].c)
    float s0 = ((F(0, x) + F(1, x)) + (F(2, x) + F(3, x))) + ((F(4, x) + F(5, x)) + (F(6, x) + F(7, x)));
    float s1 = ((F(0, y) + F(1, y)) + (F(2, y) + F(3, y))) + ((F(4, y) + F(5, y)) + (F(6, y) + F(7, y)));
    float s2 = ((F(0, z) + F(1, z)) + (F(2, z) + F(3, z))) + ((F(4, z) + F(5, z)) + (F(6, z) + F(7, z)));
#undef F
#pragma unroll
    for (int o = 16; o > 1; o >>= 1) {
        s0 += __shfl_xor_sync(0xffffffffu, s0, o);
        s1 += __shfl_xor_sync(0xffffffffu, s1, o);
        s2 += __shfl_xor_sync(0xffffffffu, s2, o);
    }
    return lane < 2 ? s0 : lane < 4 ? s1 : s2;
}

struct Params {
    uint32_t sched[NPOS];
    uint32_t stagger;
    uint32_t probe_deadline;
    const __nv_bfloat16* b2;
    CUtensorMap m_wq, m_k, m_v, m_wo, m_w1, m_w2, m_w1x;
};

__global__ void __launch_bounds__(NTHREADS, 1)
fused_kernel(const __nv_bfloat16* __restrict__ p_wmod, const __nv_bfloat16* __restrict__ p_c, const __nv_bfloat16* __restrict__ p_x,
             uint4* const box, const __nv_bfloat16* __restrict__ p_b1, __nv_bfloat16* __restrict__ p_out,
             const __grid_constant__ Params P) {
    extern __shared__ __align__(1024) unsigned char smem[];
    uint32_t t_start;
    asm volatile("mov.u32 %0, %globaltimer_lo;" : "=r"(t_start));
    uint32_t tid = threadIdx.x, warp = tid >> 5, lane = tid & 31;
    uint32_t cta = blockIdx.x;
    const uint32_t sb = smem_u32(smem);
#define BAR(i) (sb + SM_BAR + (i) * 8)
    if (warp < NCW && cta < NMOD) {
        const uint32_t row = warp * 48 + (lane >> 2);
        const char* src = reinterpret_cast<const char*>(p_wmod) + (row * (6 * D * 2) + cta * 64 + (lane & 3) * 16);
        const uint32_t d = sb + SM_M + row * 64 + (((lane & 3) ^ ((lane >> 3) & 3)) << 4);
#pragma unroll
        for (int k = 0; k < 6; k++) cp16(d + k * 512, src + k * 8 * (6 * D * 2));
    }
    uint32_t grp = cta >> 3, rk = cta & 7;

    if (warp == NCW) {
        const uint32_t sc = P.sched[min(lane, NPOS - 1u)], stagger = P.stagger;
        const int i = sc & 63;
        int mapi = 1, c0 = 0, c1, bytes = 16384, fbar = -1;
        uint32_t dst;
        if (i < IT_K) {
            mapi = 0; c0 = cta * 32; c1 = (i - IT_WQ) * 192; dst = SM_WQ + (i - IT_WQ) * 12288; bytes = 12288;
        } else if (i < IT_WO) {
            const int k = (i - IT_K) & 7;
            c1 = (grp * SK + (SK - WIN) + ((k >> 1) * 16 + rk * 2 + (k & 1)) * 64) * 2;
            dst = SM_K + k * 16384;
            if (i >= IT_V) {
                mapi = 2; dst = SM_RING + (k < 5 ? k : k - 5) * 16384;
                fbar = k == 0 ? BF_WQ : k >= 5 ? BF_V0 + k - 5 : -1;
            }
        } else if (i < IT_W2) {
            mapi = 3; c1 = (grp * 256 + (i - IT_WO) * 128 + rk * 16) * 9; dst = SM_WO + (i - IT_WO) * 18432; bytes = 18432;
            fbar = BF_K;
        } else if (i < IT_W1) {
            mapi = 5; c1 = (cta * 32 + (i - IT_W2) * 16) * 9; dst = SM_W2 + (i - IT_W2) * 18432; bytes = 18432;
        } else if (i < IT_W2C) {
            mapi = 4; c0 = cta * 32; c1 = (i - IT_W1) * 192; dst = SM_W1 + (i - IT_W1) * 12288; bytes = 12288;
        } else if (i == IT_W2C) {
            mapi = 5; c1 = (4096 + (cta - NRED) * 16) * 9; dst = SM_W2 + 2 * 18432; bytes = cta >= NRED ? 18432 : 0;
        } else {
            mapi = 6; c0 = 4096 + (cta - NRED) * 16; c1 = 0; dst = SM_W1X; bytes = cta >= NRED ? 18432 : 0;
            fbar = BF_X;
        }
        uint64_t pol;
        asm volatile("createpolicy.fractional.L2::evict_first.b64 %0, 1.0;" : "=l"(pol));
        const uint32_t t_iss = t_start + (sc >> 16) + ((((sc >> 12) & 15) * ((cta + 32) & 127) * stagger) >> 10);
        const CUtensorMap* map = &P.m_wq + mapi;
        const uint32_t gates = ((sc >> 6) & 63) | ((uint32_t)(fbar & 63) << 8);
        asm volatile("bar.sync 2, %0;" ::"n"(NTHREADS) : "memory");
#pragma unroll 1
        for (int k = 0; k < NPOS; k++) {
            const uint32_t gk = __shfl_sync(0xffffffffu, gates, k);
            const uint32_t tk = __shfl_sync(0xffffffffu, t_iss, k);
            if ((gk & 63) != IT_NONE) mbar_wait(BAR(gk & 63));
            if ((gk >> 8) != IT_NONE) mbar_wait(BAR(gk >> 8));
            uint32_t now;
            unsigned n = 0;
            do { asm volatile("mov.u32 %0, %globaltimer_lo;" : "=r"(now)); } while ((int)(now - tk) < 0 && ++n < SPIN_MAX);
            if (lane == k && bytes) {
                const uint32_t bk = BAR(i);
                mbar_expect_tx(bk, bytes);
                tma2d(sb + dst, map, c0, c1, bk, pol);
                if (mapi == 6) { tma2d(sb + dst + 6144, map, c0, 192, bk, pol); tma2d(sb + dst + 12288, map, c0, 384, bk, pol); }
            }
            __syncwarp();
        }
        return;
    }

    if (warp > NCW) {
        if (lane == 0) {
#pragma unroll
            for (int i = 0; i < NBAR_USED; i++) mbar_init(BAR(i), i == IT_M ? NCT : i >= BF_X ? 4 : 1);
            asm volatile("fence.mbarrier_init.release.cluster;" ::: "memory");
        }
        __syncwarp();
        asm volatile("bar.arrive 2, %0;" ::"n"(NTHREADS) : "memory");
        st_msg(box + half_of(BX_O + cta * 512, (lane >> 1) & 1) + 128 + (lane >> 2) * 16 + (lane & 1), 0u, 0u, 0u, 0u);
        uint32_t epoch;
        asm volatile("ld.relaxed.gpu.global.u32 %0, [%1];" : "=r"(epoch) : "l"(box + BX_EPOCH) : "memory");
        if (lane < 7) asm volatile("prefetch.tensormap [%0];" ::"l"(&P.m_wq + lane) : "memory");
        lane = __shfl_sync(0xffffffffu, lane, lane); cta = __shfl_sync(0xffffffffu, cta, 0);
        if (lane == 0) {
            uint32_t best0 = 0xffffffffu, best1 = 0xffffffffu, prev = 0;
            int wins = 0;
            bool clear = false;
#pragma unroll 1
            for (uint32_t r = 0; r < 80; r++) {
                uint32_t c0, c1 = 0;
                asm volatile("{\n.reg .pred p;\n.reg .u32 v;\nmov.u32 %0, %clock;\natom.relaxed.gpu.global.exch.b32 v, [%2], 0;\n"
                             "setp.ne.u32 p, v, 1;\n@p mov.u32 %1, %clock;\n}" : "=r"(c0), "+r"(c1)
                             : "l"(box + half_of(BX_O + cta * 512, r & 1) + 128 + ((r >> 1) & 7) * 16) : "memory");
                const uint32_t d = c1 - c0;
                if (r & 1) best1 = min(best1, d); else best0 = min(best0, d);
                if (r >= 3) wins += ((d < prev) == (r & 1)) ? 1 : -1;
                prev = d;
                const uint32_t lo = min(best0, best1), hi = max(best0, best1);
                clear = lo < 380 && lo * 10 < hi * 8;
                uint32_t now;
                asm volatile("mov.u32 %0, %globaltimer_lo;" : "=r"(now));
                if (r >= 3 && (clear || now - t_start > P.probe_deadline)) break;
            }
            uint32_t smid;
            asm volatile("mov.u32 %0, %smid;" : "=r"(smid));
            const uint32_t side = (clear || wins == 0) ? best1 < best0 : wins > 0;
            asm volatile("st.relaxed.gpu.global.u32 [%0], %1;" ::"l"(reinterpret_cast<uint32_t*>(box + BX_SIDE) + cta),
                         "r"(((epoch * 2 + 1) << 16) | ((smid >> 1) << 2) | (clear ? 2u : 0u) | side) : "memory");
        }
        __syncwarp();
        const uint32_t tag = epoch * 2 + 1;
        const uint32_t rcol = min(48 * (cta >> 3) + 8 * min(lane, 5u) + (cta & 7), D - 1u);
        const uint32_t rx = ldg16(p_x + rcol), rb2 = ldg16(P.b2 + rcol);
        const uint32_t rb1 = ldg16(p_b1 + cta * 32 + lane), rb1x = ldg16(p_b1 + 4096 + (cta & 31) * 16 + (lane & 15));
        __nv_bfloat16* const op = p_out + rcol;
        uint2* const x2_dst = reinterpret_cast<uint2*>(box + half_of(BX_X2 + ((lane >> 3) & 1) * 512, lane >> 1) + ((lane >> 2) & 1) * 128) +
                              (cta * 2 + (lane & 1));
        if (cta < NRED && lane < 16) st_msg8(x2_dst, 0u, 0u);
        mbar_wait(BAR(IT_K + 4));
        float ga, gb;
        {
            const uint4 va = poll_msg<200>(box + BX_MOD + (2 * D + rcol) / 4, tag), vb = poll_msg<200>(box + BX_MOD + (5 * D + rcol) / 4, tag);
            const uint32_t ua = rcol & 2 ? va.y : va.x, ub = rcol & 2 ? vb.y : vb.x;
            ga = rcol & 1 ? bhi(ua) : blo(ua);
            gb = rcol & 1 ? bhi(ub) : blo(ub);
        }
        asm volatile("bar.sync 3, %0;" ::"n"(NCT + 32) : "memory");
        const uint32_t side = lds32(sb + SM_XN + cta * 4);
        const uint4* part_src = box + (half_of(BX_PART + min(cta, NRED - 1u) * 512, side) + lane);
        {
            const uint4* src = box + (half_of(BX_O + cta * 512, side) + lane);
            mbar_wait(BAR(IT_V + 7));
            uint4 v[4];
            poll_slots<4>(src, tag, v);
            float o0 = (__uint_as_float(v[0].x) + __uint_as_float(v[1].x)) + (__uint_as_float(v[2].x) + __uint_as_float(v[3].x));
            float o1 = (__uint_as_float(v[0].y) + __uint_as_float(v[1].y)) + (__uint_as_float(v[2].y) + __uint_as_float(v[3].y));
            const float o = (lane < 16 ? o0 : o1) + __shfl_xor_sync(0xffffffffu, lane < 16 ? o1 : o0, 16);
            sts16(sb + SM_O + lane * 2, f2b(o));
            asm volatile("bar.arrive 10, %0;" ::"n"(NCT + 32) : "memory");
        }
        float r_x2 = 0.f;
        if (cta < NRED) {
            mbar_wait(BAR(IT_WO + 1));
            const float sv = reduce_part(part_src, tag, lane);
            r_x2 = rb(blo(rx) + rb(ga * rb(sv)));
            const uint32_t w = __float_as_uint(r_x2);
            const uint32_t w0 = __shfl_sync(0xffffffffu, w, lane & 1), w1 = __shfl_sync(0xffffffffu, w, (lane & 1) + 2),
                           w2 = __shfl_sync(0xffffffffu, w, (lane & 1) + 4);
            if (lane < 16) st_msg8(x2_dst, (w0 >> 16) | w1, (w2 >> 16) | (tag << 16));
            __syncwarp();
            asm volatile("bar.arrive 9, 224;" ::: "memory");
        }
        {
            asm volatile("bar.sync 8, %0;" ::"n"(NCT + 32) : "memory");
            uint32_t hv[2];
#pragma unroll
            for (int k = 0; k < 2; k++) {
                const uint32_t ra = sb + SM_RED + (k ? 32 + (lane & 15) : lane) * 48;
                const float4 p0 = ldsf4(ra), p1 = ldsf4(ra + 16), p2 = ldsf4(ra + 32);
                const float r = ((p0.x + p0.y) + (p0.z + p0.w)) + ((p1.x + p1.y) + (p1.z + p1.w)) + ((p2.x + p2.y) + (p2.z + p2.w));
                const float u = rb(rb(r) + blo(k ? rb1x : rb1));
                const float z = 1.5957691216057308f * (u + 0.044715f * u * u * u);
                hv[k] = f2b(u * sigm(z));
            }
            sts16(sb + SM_O + lane * 2, hv[0]);
            if (lane < 16) sts16(sb + SM_O + 64 + lane * 2, hv[1]);
            __syncwarp();
            asm volatile("bar.arrive 6, %0;" ::"n"(NCT + 32) : "memory");
        }
        if (cta < NRED) {
            mbar_wait(BAR(IT_W2 + 1));
            const float sv = reduce_part(part_src, tag + 1, lane);
            const uint32_t y = f2b(r_x2 + rb(gb * rb(rb(sv) + blo(rb2))));
            if (lane < 6) asm volatile("st.global.u16 [%0], %1;" ::"l"(op), "r"(y) : "memory");
            if (cta == 0 && lane == 0) asm volatile("st.relaxed.gpu.global.u32 [%0], %1;" ::"l"(box + BX_EPOCH), "r"(epoch + 1) : "memory");
        }
        return;
    }

    tid = __shfl_sync(0xffffffffu, tid, lane); cta = __shfl_sync(0xffffffffu, cta, 0);
    warp = tid >> 5; lane = tid & 31; grp = cta >> 3; rk = cta & 7;
    const uint32_t t = lane & 3, gq = lane >> 2;
    const uint32_t li = tid - 64;
    const bool is_ln = li < 192;
    const uint32_t lcol = is_ln ? 48 * (li >> 4) + 8 * (li & 1) + ((li >> 1) & 7) : 0;
    const uint32_t vi = warp * 24 + min(lane, 23u);
    uint32_t cv, epoch, x0, x1, x2;
    asm volatile("ld.global.nc.u32 %0, [%1];" : "=r"(cv) : "l"(reinterpret_cast<const uint32_t*>(p_c) + vi));
    asm volatile("ld.relaxed.gpu.global.u32 %0, [%1];" : "=r"(epoch) : "l"(box + BX_EPOCH) : "memory");
    x0 = ldg16(p_x + lcol); x1 = ldg16(p_x + lcol + 16); x2 = ldg16(p_x + lcol + 32);
    asm volatile("cp.async.commit_group;" ::: "memory");
    asm volatile("bar.sync 2, %0;" ::"n"(NTHREADS) : "memory");
    cp_arrive(BAR(IT_M));
    if (warp == 8) {
        const uint32_t idx = lane < 8 ? BX_MOD + cta * 8 + lane : lane < 16 ? BX_Q + cta * 8 + lane - 8 : BX_ML + cta * 2 + lane - 16;
        if (lane < 18 && (lane >= 8 || cta < NMOD)) st_msg(box + idx, 0u, 0u, 0u, 0u);
    }
    uint32_t a[6];
    {
        PIN(cv);
        const float c0 = blo(cv), c1 = bhi(cv);
        const uint32_t av = pack2(c0 * sigm(c0), c1 * sigm(c1));
#pragma unroll
        for (int i = 0; i < 6; i++) a[i] = __shfl_sync(0xffffffffu, av, i * 4 + t);
    }
    const uint32_t scr_w = sb + SM_SMALL + (warp - 2) * 8;
    PIN(x0); PIN(x1); PIN(x2);
    if (is_ln) {
        const float3 xv = layernorm3(make_float3(blo(x0), blo(x1), blo(x2)), sb + SM_SMALL + 192, scr_w + 192, lane);
        sts16(sb + SM_XN + lcol * 2, __float_as_uint(xv.x) >> 16);
        sts16(sb + SM_XN + lcol * 2 + 32, __float_as_uint(xv.y) >> 16);
        sts16(sb + SM_XN + lcol * 2 + 64, __float_as_uint(xv.z) >> 16);
    }
    const uint32_t tag = epoch * 2 + 1, tag2 = epoch * 2 + 2;
    const uint32_t red_w = sb + SM_RED + warp * 160 + lane * 8, red_r = sb + SM_RED + min(tid, 39u) * 4;
    const uint32_t r4 = warp * 48 + lane, r2 = warp * 48 + 32 + (lane & 15);

    asm volatile("cp.async.wait_group 0;" ::: "memory");
    asm volatile("fence.proxy.async.shared::cta;" ::: "memory");
    __syncwarp();
    const bool extra = cta >= NRED;
    const uint32_t w1row = warp * 48 + (lane & 7) + 8 * (lane >> 4);
#pragma unroll 1
    for (uint32_t ph = cta < NMOD ? 0 : 1; ph < 2; ph++) {
        if (ph) {
            cbar();
            const uint32_t l24 = min(lane, 23u), sl = (l24 >= 12 ? 132 : 0) + warp * 12 + l24;
            mbar_wait(BAR(IT_WQ + 1));
            const uint4 v = poll_msg<250>(box + BX_MOD + sl, tag);
            sts64(sb + SM_MOD + sl * 8, v.x, v.y);
            __syncwarp();
            const uint32_t xn = lds32(sb + SM_XN + vi * 4), sa = lds32(sb + SM_MOD + vi * 4), ca = lds32(sb + SM_MOD + 1152 + vi * 4);
            const uint32_t one = pack2(1.f + blo(ca), 1.f + bhi(ca));
            const uint32_t pr = pack2(blo(xn) * blo(one), bhi(xn) * bhi(one));
            const uint32_t av = pack2(blo(pr) + blo(sa), bhi(pr) + bhi(sa));
#pragma unroll
            for (int i = 0; i < 6; i++) a[i] = __shfl_sync(0xffffffffu, av, i * 4 + t);
            mbar_wait(BAR(IT_WQ + (warp >> 2)));
        }
        uint32_t b[4][6];
        strip_load<4>(sb + SM_M + ph * 36864 + r4 * 64, sb + SM_M + ph * 36864 + r2 * 64, (lane >> 1) & 3, b);
        const float r = strip_mma<4>(a, b, red_w, red_r, lane);
        if (warp == 0) {
            sts16(sb + SM_O + lane * 2, f2b(r));
            __syncwarp();
            if (lane < 8) st_msg(box + (ph ? BX_Q : BX_MOD) + cta * 8 + lane, lds32(sb + SM_O + lane * 8), lds32(sb + SM_O + lane * 8 + 4), 0u, tag);
        }
    }
    if (tid == 0) mbar_arrive(BAR(BF_WQ));
    if (li < 64) {
        const uint4 v = poll_msg<200>(box + BX_Q + grp * 64 + li, tag);
        sts64(sb + SM_Q + li * 8, v.x, v.y);
    }
    cbar();
    const uint32_t ob = sb + SM_O + t * 4;

    if (warp < 8) {
        uint32_t bq[4][2];
        const uint32_t msk = gq < 4 ? 0xffffffffu : 0u;
#pragma unroll
        for (int ks = 0; ks < 4; ks++) {
            const uint32_t qa = sb + SM_Q + ((gq & 1) * 64 + (gq & 2) * 16 + ks * 8 + t) * 4;
            bq[ks][0] = lds32(qa) & msk;
            bq[ks][1] = lds32(qa + 16) & msk;
        }
        float mx0 = -INFINITY, mx1 = -INFINITY;
        uint32_t rowaddr = sb + SM_K + (warp * 16 + (lane & 15)) * 128;
        const uint32_t xo = (lane >> 4) ^ (lane & 7);
        uint32_t sa = sb + SM_S + (warp * 8 + (lane >> 3)) * 4;
#pragma unroll 1
        for (int ch = 0; ch < 8; ch += 2) {
            uint32_t ka[2][4][4];
#pragma unroll
            for (int u = 0; u < 2; u++) {
                mbar_wait(BAR(IT_K + ch + u));
#pragma unroll
                for (int ks = 0; ks < 4; ks++) ldsm4(rowaddr + u * 16384 + (((2 * ks) ^ xo) << 4), ka[u][ks]);
            }
            float c[2][4];
#pragma unroll
            for (int u = 0; u < 2; u++) c[u][0] = c[u][1] = c[u][2] = c[u][3] = 0.f;
#pragma unroll
            for (int ks = 0; ks < 4; ks++)
#pragma unroll
                for (int u = 0; u < 2; u++)
                    mma16(c[u], ka[u][ks][0], ka[u][ks][1], ka[u][ks][2], ka[u][ks][3], bq[ks][0], bq[ks][1]);
            const float sc = 0.08838834764831845f;
#pragma unroll
            for (int u = 0; u < 2; u++) {
#pragma unroll
                for (int i = 0; i < 4; i++) c[u][i] = rb(rb(c[u][i] + __shfl_down_sync(0xffffffffu, c[u][i], 5)) * sc);
                if ((lane & 7) == 0) {
                    const uint32_t d = sa + u * 256;
                    stsf(d, c[u][0]); stsf(d + 2048, c[u][1]); stsf(d + 16, c[u][2]); stsf(d + 2064, c[u][3]);
                }
                mx0 = fmaxf(mx0, fmaxf(c[u][0], c[u][2]));
                mx1 = fmaxf(mx1, fmaxf(c[u][1], c[u][3]));
            }
            rowaddr += 32768; sa += 512;
        }
#pragma unroll
        for (int o = 8; o <= 16; o <<= 1) {
            mx0 = fmaxf(mx0, __shfl_xor_sync(0xffffffffu, mx0, o));
            mx1 = fmaxf(mx1, __shfl_xor_sync(0xffffffffu, mx1, o));
        }
        if (lane == 0) { stsf(sb + SM_SMALL + warp * 4, mx0); stsf(sb + SM_SMALL + 32 + warp * 4, mx1); }
        asm volatile("bar.sync 5, 256;" ::: "memory");
        if (tid == 0) mbar_arrive(BAR(BF_K));
        const uint32_t hd = warp >> 2;
        const float4 ma = ldsf4(sb + SM_SMALL + hd * 32), mb = ldsf4(sb + SM_SMALL + hd * 32 + 16);
        const float4 s4 = ldsf4(sb + SM_S + tid * 16);
        const float m = fmaxf(fmaxf(fmaxf(ma.x, ma.y), fmaxf(ma.z, ma.w)), fmaxf(fmaxf(mb.x, mb.y), fmaxf(mb.z, mb.w)));
        const float p0 = ex2((s4.x - m) * LOG2E), p1 = ex2((s4.y - m) * LOG2E), p2 = ex2((s4.z - m) * LOG2E), p3 = ex2((s4.w - m) * LOG2E);
        sts64(sb + SM_P + tid * 8, pack2(p0, p1), pack2(p2, p3));
        float l = (p0 + p1) + (p2 + p3);
#pragma unroll
        for (int o = 16; o > 0; o >>= 1) l += __shfl_xor_sync(0xffffffffu, l, o);
        if (lane == 0) { stsf(sb + SM_SMALL + 128 + warp * 4, l); stsf(sb + SM_SMALL + 160 + hd * 4, m); }
        asm volatile("bar.sync 5, 256;" ::: "memory");
    }

    uint32_t wad[3];
#pragma unroll
    for (int i = 0; i < 3; i++) {
        const uint32_t T = warp * 3 + i, blk = T >> 2, ch = 2 * (T & 3) + ((lane >> 3) & 1);
        const uint32_t fr = ((lane & 7) + 8 * (lane >> 4)) * 9 + blk;
        wad[i] = sb + fr * 128 + ((ch ^ (fr & 7)) << 4);
        PIN(wad[i]);
    }
    if (warp < 4) {
        float c[2][4];
#pragma unroll
        for (int i = 0; i < 2; i++) c[i][0] = c[i][1] = c[i][2] = c[i][3] = 0.f;
        const uint32_t row = (lane & 7) + 8 * (lane >> 4);
        const uint32_t off = sb + SM_RING + row * 128 + (((2 * warp + ((lane >> 3) & 1)) ^ (lane & 7)) << 4);
        uint32_t pp = sb + SM_P + ((gq & 1) * 512 + t) * 2;
        const uint32_t mul = gq < 2 ? 1u : gq < 4 ? 65536u : 0u;
        float f0 = 0.f, f1 = 0.f;
        uint4* o_dst = box;
        uint32_t slot = 0;
#pragma unroll 1
        for (int ch = 0; ch < 8; ch++) {
            uint32_t bp[16];
#pragma unroll
            for (int i = 0; i < 16; i++) bp[i] = lds16(pp + i * 8) * mul;
            if (ch == 7) {
                asm volatile("bar.sync 3, %0;" ::"n"(NCT + 32) : "memory");
                f0 = ldsf(sb + SM_SMALL + 176); f1 = ldsf(sb + SM_SMALL + 180);
                const uint32_t ro = grp * 8 + (t & 1) * 4 + warp;
                o_dst = box + (half_of(BX_O + ro * 512, lds32(sb + SM_XN + ro * 4)) + rk * 16 + gq);
            }
            uint32_t base = off + slot * 16384;
            PIN(base);
            mbar_wait(BAR(IT_V + ch));
            uint32_t va[8][4];
#pragma unroll
            for (int ks = 0; ks < 8; ks++) ldsm4t(base + ks * 2048, va[ks]);
#pragma unroll
            for (int ks = 0; ks < 8; ks++) mma16(c[ks & 1], va[ks][0], va[ks][1], va[ks][2], va[ks][3], bp[2 * ks], bp[2 * ks + 1]);
            if ((ch < 3 || ch == 4) && lane == 0) mbar_arrive(BAR(ch == 4 ? BF_X : BF_V0 + ch));
            slot = slot == 4 ? 0 : slot + 1;
            pp += 128;
        }
        if (t < 2) {
            st_msg(o_dst, __float_as_uint((c[0][0] + c[1][0]) * f0), __float_as_uint((c[0][1] + c[1][1]) * f1), 0u, tag);
            st_msg(o_dst + 8, __float_as_uint((c[0][2] + c[1][2]) * f0), __float_as_uint((c[0][3] + c[1][3]) * f1), 0u, tag);
        }
    } else {
        if (warp == 4) {
            const uint32_t hd = lane & 1;
            const float m_own = ldsf(sb + SM_SMALL + 160 + hd * 4);
            const float4 l4 = ldsf4(sb + SM_SMALL + 128 + hd * 16);
            if (lane < 2) st_msg(box + BX_ML + cta * 2 + lane, __float_as_uint(m_own), __float_as_uint((l4.x + l4.y) + (l4.z + l4.w)), 0u, tag);
            mbar_wait(BAR(IT_V + 3));
            const uint4 v = poll_msg<300>(box + BX_ML + grp * 16 + (lane & 15), tag);
            const float ms = __uint_as_float(v.x);
            float M = ms;
#pragma unroll
            for (int o = 2; o <= 8; o <<= 1) M = fmaxf(M, __shfl_xor_sync(0xffffffffu, M, o));
            float L = __uint_as_float(v.y) * ex2((ms - M) * LOG2E);
#pragma unroll
            for (int o = 2; o <= 8; o <<= 1) L += __shfl_xor_sync(0xffffffffu, L, o);
            if (lane < 2) stsf(sb + SM_SMALL + 176 + lane * 4, ex2((m_own - M) * LOG2E) * rcp(L));
        } else if (warp >= 8) {
#pragma unroll 1
            for (uint32_t i = tid - 256; i < 288; i += 128) {
                const uint4 v = poll_msg<200>(box + BX_MOD + 432 + i, tag);
                sts64(sb + SM_MOD + i * 8, v.x, v.y);
            }
            mbar_wait(BAR(IT_V + 2));
            const uint32_t u = tid - 256;
            const uint32_t* side = reinterpret_cast<const uint32_t*>(box + BX_SIDE) + u;
            uint32_t sp;
            unsigned n = 0;
#pragma unroll 1
            do {
                if (n) __nanosleep(500);
                asm volatile("ld.relaxed.gpu.global.u32 %0, [%1];" : "=r"(sp) : "l"(side) : "memory");
            } while (__any_sync(0xffffffffu, (sp >> 16) != (tag & 0xffffu)) && ++n < SPIN_MAX);
            const uint32_t nb = __shfl_xor_sync(0xffffffffu, sp, 1);
            sts32(sb + SM_XN + u * 4, (((sp ^ nb) >> 1) == 1 && (nb & 2) ? nb : sp) & 1);
            asm volatile("bar.sync 7, 128;" ::: "memory");
#pragma unroll
            for (int k = 0; k < 2; k++) {
                const uint32_t rp = k * 64 + (u >> 1);
                if (rp < NRED) st_msg(box + (half_of(BX_PART + rp * 512, lds32(sb + SM_XN + rp * 4)) + cta * 2 + (u & 1)), 0u, 0u, 0u, 0u);
            }
            const uint32_t ro = grp * 8 + (u >> 4);
            st_msg(box + (half_of(BX_O + ro * 512, lds32(sb + SM_XN + ro * 4)) + rk * 16 + (u & 15)), 0u, 0u, 0u, 0u);
            asm volatile("bar.arrive 3, %0;" ::"n"(NCT + 32) : "memory");
        }
        if (warp < 8) asm volatile("bar.sync 3, %0;" ::"n"(NCT + 32) : "memory");
    }

    uint4* const part_dst = box + (half_of(BX_PART + (warp * 8 + gq) * 512, lds32(sb + SM_XN + (warp * 8 + gq) * 4)) + cta * 2 + (t & 1));
    const uint32_t my_side = lds32(sb + SM_XN + cta * 4);
    {
        uint32_t wa[3][8];
        mbar_wait(BAR(IT_WO));
#pragma unroll
        for (int i = 0; i < 3; i++) ldsm4t(wad[i] + SM_WO, &wa[i][0]);
        const bool pre0 = mbar_test(BAR(IT_WO + 1));
        if (pre0) {
#pragma unroll
            for (int i = 0; i < 3; i++) ldsm4t(wad[i] + SM_WO + 16 * 1152, &wa[i][4]);
        }
        asm volatile("bar.sync 10, %0;" ::"n"(NCT + 32) : "memory");
        const uint32_t b0 = lds32(ob), b1 = lds32(ob + 16), b2 = lds32(ob + 32), b3 = lds32(ob + 48);
        float c[3][4];
#pragma unroll
        for (int i = 0; i < 3; i++) {
            c[i][0] = c[i][1] = c[i][2] = c[i][3] = 0.f;
            mma16(c[i], wa[i][0], wa[i][1], wa[i][2], wa[i][3], b0, b1);
        }
        if (!pre0) {
            mbar_wait(BAR(IT_WO + 1));
#pragma unroll
            for (int i = 0; i < 3; i++) ldsm4t(wad[i] + SM_WO + 16 * 1152, &wa[i][4]);
        }
#pragma unroll
        for (int i = 0; i < 3; i++) mma16(c[i], wa[i][4], wa[i][5], wa[i][6], wa[i][7], b2, b3);
        if (t < 2) st_msg(part_dst, __float_as_uint(t ? c[0][2] : c[0][0]), __float_as_uint(t ? c[1][2] : c[1][0]),
                          __float_as_uint(t ? c[2][2] : c[2][0]), tag);
    }
    uint32_t wb[6][4], wx[3][4];
    const uint32_t w1bar = BAR((lane & 1) && extra ? IT_W1X : IT_W1 + (warp >> 2));
    const uint32_t w1a = sb + SM_W1 + w1row * 64 + ((((lane >> 3) & 1) ^ ((lane >> 1) & 3)) << 4);
    const uint32_t w1x = sb + SM_W1X + w1row * 32 + ((lane >> 3) & 1) * 16;
#define W1_LOAD() do { _Pragma("unroll") for (int k = 0; k < 3; k++) { \
        if (extra) ldsm4t(w1x + k * 512, wx[k]); \
        ldsm4t(w1a + k * 1024, wb[k * 2]); ldsm4t((w1a ^ 32) + k * 1024, wb[k * 2 + 1]); } } while (0)
    bool pre1 = false;
    if (is_ln) {
        const uint32_t ma = sb + SM_MOD + lcol * 2;
        float c0 = rb(1.f + blo(lds16(ma + 2 * D))), c1 = rb(1.f + blo(lds16(ma + 2 * D + 32))), c2 = rb(1.f + blo(lds16(ma + 2 * D + 64)));
        float s0 = blo(lds16(ma)), s1 = blo(lds16(ma + 32)), s2 = blo(lds16(ma + 64));
        const uint2* src = reinterpret_cast<const uint2*>(box + half_of(BX_X2 + (cta & 2) * 256, my_side) + (cta & 1) * 128) + li;
        const uint32_t yd = sb + SM_VEC + lcol * 2;
        uint2 v;
        bool xp = true;
        unsigned n = 0;
        if (cta < NRED) asm volatile("bar.sync 9, 224;" ::: "memory");
        else mbar_wait(w1bar);
        pre1 = mbar_test(w1bar);
        if (pre1) W1_LOAD();
#pragma unroll 1
        do { if (xp) v = ld_msg8(src); xp = (v.y >> 16) != (tag & 0xffffu); } while (__any_sync(0xffffffffu, xp) && ++n < SPIN_MAX);
        float3 y = layernorm3(make_float3(blo(v.x), bhi(v.x), blo(v.y)), sb + SM_SMALL, scr_w, lane);
        y = layernorm3(make_float3(rb(rb(y.x * c0) + s0), rb(rb(y.y * c1) + s1), rb(rb(y.z * c2) + s2)), sb + SM_SMALL + 64, scr_w + 64, lane);
        sts16(yd, __float_as_uint(y.x) >> 16); sts16(yd + 32, __float_as_uint(y.y) >> 16); sts16(yd + 64, __float_as_uint(y.z) >> 16);
    }
    {
        const uint32_t ya = sb + SM_VEC + (warp * 24 + t) * 4;
        const uint32_t rd = sb + SM_RED + (t * 16 + gq) * 48 + warp * 4;
        if (!pre1) {
            mbar_wait(w1bar);
            __syncwarp();
            W1_LOAD();
        }
        cbar();
#pragma unroll
        for (int i = 0; i < 6; i++) a[i] = lds32(ya + i * 16);
        float c[3][4];
#pragma unroll
        for (int j = 0; j < 3; j++) c[j][0] = c[j][1] = c[j][2] = c[j][3] = 0.f;
#pragma unroll
        for (int k = 0; k < 3; k++) {
#pragma unroll
            for (int j = 0; j < 2; j++) mma16(c[j], wb[k * 2 + j][0], wb[k * 2 + j][1], wb[k * 2 + j][2], wb[k * 2 + j][3], a[2 * k], a[2 * k + 1]);
            if (extra) mma16(c[2], wx[k][0], wx[k][1], wx[k][2], wx[k][3], a[2 * k], a[2 * k + 1]);
        }
        if (t < 3) {
            stsf(rd, t == 0 ? c[0][0] : t == 1 ? c[1][0] : c[2][0]);
            stsf(rd + 8 * 48, t == 0 ? c[0][2] : t == 1 ? c[1][2] : c[2][2]);
        }
        asm volatile("bar.arrive 8, %0;" ::"n"(NCT + 32) : "memory");
    }
    {
        uint32_t wa[3][12];
        mbar_wait(BAR((lane & 1) && extra ? IT_W2C : IT_W2));
        __syncwarp();
#pragma unroll
        for (int i = 0; i < 3; i++) {
            ldsm4t(wad[i] + SM_W2, &wa[i][0]);
            if (extra) ldsm4t(wad[i] + SM_W2 + 32 * 1152, &wa[i][8]);
        }
        const bool pre = mbar_test(BAR(IT_W2 + 1));
        if (pre) {
#pragma unroll
            for (int i = 0; i < 3; i++) ldsm4t(wad[i] + SM_W2 + 16 * 1152, &wa[i][4]);
        }
        asm volatile("bar.sync 6, %0;" ::"n"(NCT + 32) : "memory");
        uint32_t b[6];
#pragma unroll
        for (int i = 0; i < 6; i++) b[i] = lds32(ob + i * 16);
        float c[3][4], e[3][4], f[3][4];
#pragma unroll
        for (int i = 0; i < 3; i++) {
#pragma unroll
            for (int j = 0; j < 4; j++) c[i][j] = e[i][j] = f[i][j] = 0.f;
            mma16(c[i], wa[i][0], wa[i][1], wa[i][2], wa[i][3], b[0], b[1]);
            if (extra) mma16(e[i], wa[i][8], wa[i][9], wa[i][10], wa[i][11], b[4], b[5]);
        }
        if (!pre) {
            mbar_wait(BAR(IT_W2 + 1));
#pragma unroll
            for (int i = 0; i < 3; i++) ldsm4t(wad[i] + SM_W2 + 16 * 1152, &wa[i][4]);
        }
#pragma unroll
        for (int i = 0; i < 3; i++) mma16(f[i], wa[i][4], wa[i][5], wa[i][6], wa[i][7], b[2], b[3]);
        float r[3];
#pragma unroll
        for (int i = 0; i < 3; i++) r[i] = t ? (c[i][2] + e[i][2]) + f[i][2] : (c[i][0] + e[i][0]) + f[i][0];
        if (t < 2) st_msg(part_dst, __float_as_uint(r[0]), __float_as_uint(r[1]), __float_as_uint(r[2]), tag2);
    }
#undef BAR
}

typedef CUresult (*EncodeFn)(CUtensorMap*, CUtensorMapDataType, cuuint32_t, void*, const cuuint64_t*, const cuuint64_t*,
                             const cuuint32_t*, const cuuint32_t*, CUtensorMapInterleave, CUtensorMapSwizzle,
                             CUtensorMapL2promotion, CUtensorMapFloatOOBfill);

void make_map(EncodeFn enc, CUtensorMap* m, const void* base, uint64_t cols, uint64_t rows, uint32_t bc, uint32_t br,
              CUtensorMapSwizzle sw, CUtensorMapL2promotion promo) {
    cuuint64_t dims[2] = {cols, rows};
    cuuint64_t strides[1] = {cols * 2};
    cuuint32_t box[2] = {bc, br};
    cuuint32_t es[2] = {1, 1};
    enc(m, CU_TENSOR_MAP_DATA_TYPE_BFLOAT16, 2, const_cast<void*>(base), dims, strides, box, es,
        CU_TENSOR_MAP_INTERLEAVE_NONE, sw, promo, CU_TENSOR_MAP_FLOAT_OOB_FILL_NONE);
}

struct Tune { int t0, rate, stagger, gap, rate2, win, win2, mw; char order[40], stag[40]; };
const Tune g_tune = {-1500, 2450, 670, 200, 2600, 70, 70, 20, "abcKKKKKKKKVVVVVVVVOOxdefXYX", "8888888888888888888448888888"};
void make_schedule(Params& P, double speed) {
    const Tune& T = g_tune;
    int nk = 0, nv = 0, no = 0, nx = 0, n = 0, hist[40], hb[40], nh = 0;
    bool after = false;
    const double stagger = T.stagger / speed;
    double t = T.t0 + (T.stagger - stagger) / 2 + 31104 * 100.0 / (T.rate * speed);
    hb[nh] = T.mw * 1024; hist[nh++] = IT_M;
    for (const char* c = T.order; *c && n < NPOS; c++) {
        int item, bytes;
        switch (*c) {
            case 'a': case 'b': case 'c': item = IT_WQ + (*c - 'a'); bytes = 12288; break;
            case 'K': item = IT_K + nk++; bytes = 16384; break;
            case 'V': item = IT_V + nv++; bytes = 16384; break;
            case 'O': item = IT_WO + no++; bytes = 18432; break;
            case 'd': case 'e': case 'f': item = IT_W1 + (*c - 'd'); bytes = 12288; break;
            case 'X': item = IT_W2 + nx++; bytes = 18432; break;
            case 'x': item = IT_W1X; bytes = 4608; break;
            default: item = IT_W2C; bytes = 4608; break;
        }
        t += bytes * 100.0 / ((after ? T.rate2 : T.rate) * speed);
        int j = nh - 1, sum = bytes;
        while (j >= 0 && sum + hb[j] <= (after ? T.win2 : T.win) * 1024) sum += hb[j--];
        const int gate = j >= 0 ? hist[j] : IT_NONE;
        const int sg = T.stag[n] - '0';
        int tt = (int)(t + (8 - sg) * stagger / 16.0);
        tt = tt < 0 ? 0 : tt > 65535 ? 65535 : tt;
        P.sched[n++] = (uint32_t)item | (gate << 6) | (sg << 12) | ((uint32_t)tt << 16);
        if (bytes > 8192) { hb[nh] = bytes; hist[nh++] = item; }
        if (no == 2 && nv == 8 && !after) { after = true; t += T.gap; }
    }
    P.stagger = (uint32_t)stagger;
    P.probe_deadline = (uint32_t)(9300 / speed);
}

__device__ float f_a[FF], f_mod[6 * D], f_q[4096], f_x2[D], f_t[FF];
typedef const __nv_bfloat16* CB;
__device__ __forceinline__ float bf(CB p, size_t i) { return __bfloat162float(p[i]); }
__global__ void fb_gemv(const float* v, CB w, int K, int N, float* out) {
    const int n = blockIdx.x * blockDim.x + threadIdx.x;
    if (n >= N) return;
    float s = 0.f;
    for (int k = 0; k < K; k++) s += v[k] * bf(w, (size_t)k * N + n);
    out[n] = rb(s);
}
__device__ float fb_ln(float v, float* sh) {
    __syncthreads(); sh[threadIdx.x] = v; __syncthreads();
    float s = 0.f, q = 0.f;
    for (int i = 0; i < D; i++) s += sh[i];
    s /= D;
    for (int i = 0; i < D; i++) q += (sh[i] - s) * (sh[i] - s);
    return rb(rb(v - rb(s)) / rb(sqrtf(rb(rb(q / D) + 1e-5f))));
}
__global__ void fb_elem(int stage, CB x, CB c, CB b1, CB b2, __nv_bfloat16* out) {
    __shared__ float sh[D];
    const int i = threadIdx.x;
    if (stage == 0) { const float v = bf(c, i); f_a[i] = rb(v / (1.f + expf(-v))); }
    if (stage == 1) f_a[i] = rb(rb(fb_ln(bf(x, i), sh) * rb(1.f + f_mod[D + i])) + f_mod[i]);
    if (stage == 2) {
        f_x2[i] = rb(bf(x, i) + rb(f_mod[2 * D + i] * f_t[i]));
        f_a[i] = fb_ln(rb(rb(fb_ln(f_x2[i], sh) * rb(1.f + f_mod[4 * D + i])) + f_mod[3 * D + i]), sh);
    }
    if (stage == 3)
        for (int j = i; j < FF; j += D) {
            const float u = rb(f_t[j] + bf(b1, j));
            f_a[j] = rb(0.5f * u * (1.f + tanhf(0.7978845608028654f * (u + 0.044715f * u * u * u))));
        }
    if (stage == 4) out[i] = __float2bfloat16_rn(f_x2[i] + rb(f_mod[5 * D + i] * rb(f_t[i] + bf(b2, i))));
}
__global__ void fb_attn(CB k, CB v) {
    __shared__ float p[WIN], red[128];
    const int h = blockIdx.x, t = threadIdx.x;
    const size_t base = ((size_t)(h / 2) * SK + SK - WIN) * 128;
    float m = -INFINITY, l = 0.f, o = 0.f;
    for (int j = t; j < WIN; j += 128) {
        float s = 0.f;
        for (int d = 0; d < 128; d++) s += f_q[h * 128 + d] * bf(k, base + (size_t)j * 128 + d);
        p[j] = rb(rb(s) * 0.08838834764831845f);
        m = fmaxf(m, p[j]);
    }
    red[t] = m; __syncthreads();
    for (int i = 0; i < 128; i++) m = fmaxf(m, red[i]);
    __syncthreads();
    for (int j = t; j < WIN; j += 128) { p[j] = expf(p[j] - m); l += p[j]; }
    red[t] = l; __syncthreads();
    l = 0.f;
    for (int i = 0; i < 128; i++) l += red[i];
    for (int j = 0; j < WIN; j++) o += rb(p[j] / l) * bf(v, base + (size_t)j * 128 + t);
    f_a[h * 128 + t] = rb(o);
}
void fallback(void* const* in, void* out) {
    float *a, *mod, *q, *t;
    cudaGetSymbolAddress((void**)&a, f_a); cudaGetSymbolAddress((void**)&mod, f_mod);
    cudaGetSymbolAddress((void**)&q, f_q); cudaGetSymbolAddress((void**)&t, f_t);
#define ELEM(s) fb_elem<<<1, D>>>(s, (CB)in[0], (CB)in[10], (CB)in[7], (CB)in[9], (__nv_bfloat16*)out)
    ELEM(0); fb_gemv<<<54, 64>>>(a, (CB)in[11], D, 6 * D, mod);
    ELEM(1); fb_gemv<<<64, 64>>>(a, (CB)in[3], D, 4096, q);
    fb_attn<<<32, 128>>>((CB)in[1], (CB)in[2]); fb_gemv<<<9, 64>>>(a, (CB)in[4], 4096, D, t);
    ELEM(2); fb_gemv<<<72, 64>>>(a, (CB)in[6], D, FF, t);
    ELEM(3); fb_gemv<<<9, 64>>>(a, (CB)in[8], FF, D, t);
    ELEM(4);
#undef ELEM
}

}

extern "C" void kernel_launch(void* const* d_in, const int* in_sizes, int n_in, void* d_out, int out_size) {
    (void)in_sizes; (void)n_in; (void)out_size;
    int dev = 0, sms = 0, occ = 0, mclk = 0, bus = 0;
    cudaGetDevice(&dev);
    cudaDeviceGetAttribute(&sms, cudaDevAttrMultiProcessorCount, dev);
    cudaDeviceGetAttribute(&mclk, cudaDevAttrMemoryClockRate, dev);
    cudaDeviceGetAttribute(&bus, cudaDevAttrGlobalMemoryBusWidth, dev);
    cudaFuncSetAttribute(fused_kernel, cudaFuncAttributeMaxDynamicSharedMemorySize, SM_TOTAL);
    cudaOccupancyMaxActiveBlocksPerMultiprocessor(&occ, fused_kernel, NTHREADS, SM_TOTAL);
    void* fn = nullptr;
    cudaDriverEntryPointQueryResult qr;
    cudaGetDriverEntryPoint("cuTensorMapEncodeTiled", &fn, cudaEnableDefault, &qr);
    if (sms * occ < NATT || !fn) { (void)cudaGetLastError(); fallback(d_in, d_out); return; }
    EncodeFn enc = (EncodeFn)fn;

    Params P;
    make_map(enc, &P.m_wq, d_in[3], 4096, D, 32, 192, CU_TENSOR_MAP_SWIZZLE_64B, CU_TENSOR_MAP_L2_PROMOTION_L2_128B);
    make_map(enc, &P.m_k, d_in[1], 64, (uint64_t)HKV * SK * 2, 64, 128, CU_TENSOR_MAP_SWIZZLE_128B, CU_TENSOR_MAP_L2_PROMOTION_L2_256B);
    make_map(enc, &P.m_v, d_in[2], 64, (uint64_t)HKV * SK * 2, 64, 128, CU_TENSOR_MAP_SWIZZLE_128B, CU_TENSOR_MAP_L2_PROMOTION_L2_256B);
    make_map(enc, &P.m_wo, d_in[4], 64, 4096 * 9, 64, 144, CU_TENSOR_MAP_SWIZZLE_128B, CU_TENSOR_MAP_L2_PROMOTION_L2_256B);
    make_map(enc, &P.m_w1, d_in[6], FF, D, 32, 192, CU_TENSOR_MAP_SWIZZLE_64B, CU_TENSOR_MAP_L2_PROMOTION_L2_128B);
    make_map(enc, &P.m_w1x, d_in[6], FF, D, 16, 192, CU_TENSOR_MAP_SWIZZLE_NONE, CU_TENSOR_MAP_L2_PROMOTION_L2_64B);
    make_map(enc, &P.m_w2, d_in[8], 64, FF * 9, 64, 144, CU_TENSOR_MAP_SWIZZLE_128B, CU_TENSOR_MAP_L2_PROMOTION_L2_256B);
    P.b2 = (const __nv_bfloat16*)d_in[9];
    const double speed = mclk > 0 && bus > 0 ? (double)mclk * bus / (2619000.0 * 5120.0) : 1.0;
    make_schedule(P, speed);
    void* boxp = nullptr;
    cudaGetSymbolAddress(&boxp, g_box);
    uint4* box = (uint4*)(((uintptr_t)boxp + (2 << 20) - 1) & ~(uintptr_t)((2 << 20) - 1));
    fused_kernel<<<NATT, NTHREADS, SM_TOTAL>>>((const __nv_bfloat16*)d_in[11], (const __nv_bfloat16*)d_in[10], (const __nv_bfloat16*)d_in[0],
                                               box, (const __nv_bfloat16*)d_in[7], (__nv_bfloat16*)d_out, P);
}
```

```cpp
#include <cuda_runtime.h>
#include <cuda_bf16.h>
#include <cuda.h>
#include <stdint.h>

namespace {

constexpr int D = 576, HKV = 16, SK = 32768, WIN = 4096, FF = 4608;
constexpr int NATT = 128;
constexpr int NRED = 96;
constexpr int NMOD = 108;
constexpr int NCW = 12;
constexpr int NCT = NCW * 32;
constexpr int NTHREADS = NCT + 64;

constexpr int SM_K = 0;
constexpr int SM_WO = 0;
constexpr int SM_W2 = 36864;
constexpr int SM_W1 = 92160;
constexpr int SM_RING = 131072;
constexpr int SM_W1X = SM_RING + 3 * 16384;
constexpr int SM_M = SM_RING;
constexpr int SM_WQ = SM_RING + 36864;
constexpr int SM_MISC = SM_RING + 5 * 16384;
constexpr int SM_MOD = SM_MISC;
constexpr int SM_VEC = SM_MOD + 2304;
constexpr int SM_XN = SM_VEC + 1152;
constexpr int SM_Q = SM_XN + 1152;
constexpr int SM_S = SM_Q + 512;
constexpr int SM_P = SM_S + 4096;
constexpr int SM_RED = SM_P + 2048;
constexpr int SM_SMALL = SM_RED + 2304;
constexpr int SM_O = SM_SMALL + 256;
constexpr int SM_BAR = SM_O + 128;
constexpr int SM_TOTAL = SM_BAR + 40 * 8;
static_assert(SM_TOTAL <= 232448, "smem");

enum { IT_M = 0, IT_WQ = 1, IT_K = 4, IT_V = 12, IT_WO = 20, IT_W2 = 22, IT_W1 = 24, IT_W2C = 27, IT_W1X = 28,
       BF_WQ = 29, BF_K = 30, BF_X = 31, BF_V0 = 32  , NBAR_USED = 35, NPOS = 28, IT_NONE = 63 };

enum { BX_X2 = 0,
       BX_O = 1024,
       BX_PART = BX_O + NATT * 512,
       BX_MOD = BX_PART + NRED * 512,
       BX_Q = BX_MOD + 864,
       BX_ML = BX_Q + NATT * 8,
       BX_SIDE = BX_ML + NATT * 2,
       BX_EPOCH = BX_SIDE + 32,
       BX_TOTAL = BX_EPOCH + 8 };
static_assert(BX_TOTAL * 16 <= (2 << 20), "mailboxes stay inside one 2 MB page");
__device__ uint4 g_box[(4 << 20) / 16];
__device__ __forceinline__ uint32_t half_of(uint32_t pair, uint32_t side) {
    constexpr uint32_t MASK = ((1u << 13) | (1u << 16) | (1u << 17) | (1u << 19)) >> 4;
    return pair + (((__popc(pair & MASK) ^ side) & 1u) << 8);
}

constexpr unsigned SPIN_MAX = 1u << 21;
#define PIN(x) asm volatile("" : "+r"(x))

__device__ __forceinline__ uint32_t smem_u32(const void* p) { return (uint32_t)__cvta_generic_to_shared(p); }
__device__ __forceinline__ void mbar_init(uint32_t bar, uint32_t cnt) {
    asm volatile("mbarrier.init.shared::cta.b64 [%0], %1;" ::"r"(bar), "r"(cnt) : "memory");
}
__device__ __forceinline__ void mbar_expect_tx(uint32_t bar, uint32_t bytes) {
    asm volatile("mbarrier.arrive.expect_tx.shared::cta.b64 _, [%0], %1;" ::"r"(bar), "r"(bytes) : "memory");
}
__device__ __forceinline__ void mbar_arrive(uint32_t bar) {
    asm volatile("mbarrier.arrive.shared::cta.b64 _, [%0];" ::"r"(bar) : "memory");
}
__device__ __forceinline__ void mbar_wait(uint32_t bar) {
    uint32_t ok;
    unsigned n = 0;
#pragma unroll 1
    do {
        asm volatile("{\n.reg .pred p;\nmbarrier.try_wait.parity.shared::cta.b64 p, [%1], 0;\nselp.u32 %0, 1, 0, p;\n}"
                     : "=r"(ok) : "r"(bar) : "memory");
    } while (!ok && ++n < SPIN_MAX);
}
__device__ __forceinline__ bool mbar_test(uint32_t bar) {
    uint32_t ok;
    asm volatile("{\n.reg .pred p;\nmbarrier.test_wait.parity.shared::cta.b64 p, [%1], 0;\nselp.u32 %0, 1, 0, p;\n}"
                 : "=r"(ok) : "r"(bar) : "memory");
    return __all_sync(0xffffffffu, ok);
}
__device__ __forceinline__ void tma2d(uint32_t dst, const CUtensorMap* map, int c0, int c1, uint32_t bar, uint64_t pol) {
    asm volatile("cp.async.bulk.tensor.2d.shared::cluster.global.mbarrier::complete_tx::bytes.L2::cache_hint [%0], [%1, {%3, %4}], [%2], %5;"
                 ::"r"(dst), "l"(map), "r"(bar), "r"(c0), "r"(c1), "l"(pol) : "memory");
}
__device__ __forceinline__ void cp16(uint32_t dst, const void* src) {
    asm volatile("cp.async.cg.shared.global.L2::128B [%0], [%1], 16;" ::"r"(dst), "l"(src) : "memory");
}
__device__ __forceinline__ void cp_arrive(uint32_t bar) {
    asm volatile("cp.async.mbarrier.arrive.noinc.shared::cta.b64 [%0];" ::"r"(bar) : "memory");
}
__device__ __forceinline__ void cbar() { asm volatile("bar.sync 1, %0;" ::"n"(NCT) : "memory"); }

__device__ __forceinline__ uint32_t lds32(uint32_t a) { uint32_t v; asm volatile("ld.shared.u32 %0, [%1];" : "=r"(v) : "r"(a) : "memory"); return v; }
__device__ __forceinline__ uint32_t lds16(uint32_t a) { uint32_t v; asm volatile("ld.shared.u16 %0, [%1];" : "=r"(v) : "r"(a) : "memory"); return v; }
__device__ __forceinline__ float ldsf(uint32_t a) { float v; asm volatile("ld.shared.f32 %0, [%1];" : "=f"(v) : "r"(a) : "memory"); return v; }
__device__ __forceinline__ float4 ldsf4(uint32_t a) {
    float4 v;
    asm volatile("ld.shared.v4.f32 {%0,%1,%2,%3}, [%4];" : "=f"(v.x), "=f"(v.y), "=f"(v.z), "=f"(v.w) : "r"(a) : "memory");
    return v;
}
__device__ __forceinline__ void sts32(uint32_t a, uint32_t v) { asm volatile("st.shared.u32 [%0], %1;" ::"r"(a), "r"(v) : "memory"); }
__device__ __forceinline__ void sts16(uint32_t a, uint32_t v) { asm volatile("st.shared.u16 [%0], %1;" ::"r"(a), "r"(v) : "memory"); }
__device__ __forceinline__ void stsf(uint32_t a, float v) { asm volatile("st.shared.f32 [%0], %1;" ::"r"(a), "f"(v) : "memory"); }
__device__ __forceinline__ void sts64(uint32_t a, uint32_t x, uint32_t y) { asm volatile("st.shared.v2.u32 [%0], {%1,%2};" ::"r"(a), "r"(x), "r"(y) : "memory"); }

__device__ __forceinline__ void st_msg(uint4* p, uint32_t a, uint32_t b, uint32_t c, uint32_t d) {
    asm volatile("{\n.reg .b128 t;\n.reg .b64 lo, hi;\nmov.b64 lo, {%1, %2};\nmov.b64 hi, {%3, %4};\nmov.b128 t, {lo, hi};\n"
                 "st.relaxed.gpu.global.b128 [%0], t;\n}" ::"l"(p), "r"(a), "r"(b), "r"(c), "r"(d) : "memory");
}
__device__ __forceinline__ uint4 ld_msg(const uint4* p) {
    uint4 v;
    asm volatile("{\n.reg .b128 t;\n.reg .b64 lo, hi;\nld.relaxed.gpu.global.b128 t, [%4];\nmov.b128 {lo, hi}, t;\n"
                 "mov.b64 {%0, %1}, lo;\nmov.b64 {%2, %3}, hi;\n}" : "=r"(v.x), "=r"(v.y), "=r"(v.z), "=r"(v.w) : "l"(p) : "memory");
    return v;
}
template <int BACKOFF = 0>
__device__ __forceinline__ uint4 poll_msg(const uint4* p, uint32_t tag) {
    uint4 v;
    v.w = tag + 1;
    unsigned n = 0;
#pragma unroll 1
    do {
        if (BACKOFF && n) __nanosleep(BACKOFF);
        if (v.w != tag) v = ld_msg(p);
    } while (__any_sync(0xffffffffu, v.w != tag) && ++n < SPIN_MAX);
    return v;
}
__device__ __forceinline__ void st_msg8(uint2* p, uint32_t a, uint32_t b) {
    asm volatile("{\n.reg .b64 t;\nmov.b64 t, {%1, %2};\nst.relaxed.gpu.global.b64 [%0], t;\n}" ::"l"(p), "r"(a), "r"(b) : "memory");
}
__device__ __forceinline__ uint2 ld_msg8(const uint2* p) {
    uint2 v;
    asm volatile("{\n.reg .b64 t;\nld.relaxed.gpu.global.b64 t, [%2];\nmov.b64 {%0, %1}, t;\n}" : "=r"(v.x), "=r"(v.y) : "l"(p) : "memory");
    return v;
}
__device__ __forceinline__ uint32_t ldg16(const __nv_bfloat16* p) {
    uint32_t v;
    asm volatile("ld.global.nc.u16 %0, [%1];" : "=r"(v) : "l"(p));
    return v;
}

__device__ __forceinline__ void ldsm4(uint32_t a, uint32_t* r) {
    asm volatile("ldmatrix.sync.aligned.m8n8.x4.shared.b16 {%0,%1,%2,%3}, [%4];" : "=r"(r[0]), "=r"(r[1]), "=r"(r[2]), "=r"(r[3]) : "r"(a) : "memory");
}
__device__ __forceinline__ void ldsm4t(uint32_t a, uint32_t* r) {
    asm volatile("ldmatrix.sync.aligned.m8n8.x4.trans.shared.b16 {%0,%1,%2,%3}, [%4];" : "=r"(r[0]), "=r"(r[1]), "=r"(r[2]), "=r"(r[3]) : "r"(a) : "memory");
}
__device__ __forceinline__ void ldsm2t(uint32_t a, uint32_t* r) {
    asm volatile("ldmatrix.sync.aligned.m8n8.x2.trans.shared.b16 {%0,%1}, [%2];" : "=r"(r[0]), "=r"(r[1]) : "r"(a) : "memory");
}
__device__ __forceinline__ void mma16(float* c, uint32_t a0, uint32_t a1, uint32_t a2, uint32_t a3, uint32_t b0, uint32_t b1) {
    asm volatile("mma.sync.aligned.m16n8k16.row.col.f32.bf16.bf16.f32 {%0,%1,%2,%3}, {%4,%5,%6,%7}, {%8,%9}, {%0,%1,%2,%3};"
                 : "+f"(c[0]), "+f"(c[1]), "+f"(c[2]), "+f"(c[3]) : "r"(a0), "r"(a1), "r"(a2), "r"(a3), "r"(b0), "r"(b1));
}

__device__ __forceinline__ uint32_t pack2(float lo, float hi) {
    uint32_t r;
    asm("cvt.rn.bf16x2.f32 %0, %1, %2;" : "=r"(r) : "f"(hi), "f"(lo));
    return r;
}
__device__ __forceinline__ float rb(float x) { return __uint_as_float(pack2(0.f, x)); }
__device__ __forceinline__ uint32_t f2b(float x) { return pack2(x, 0.f); }
__device__ __forceinline__ float blo(uint32_t u) { return __uint_as_float(u << 16); }
__device__ __forceinline__ float bhi(uint32_t u) { return __uint_as_float(u & 0xffff0000u); }
__device__ __forceinline__ float ex2(float x) { float r; asm("ex2.approx.ftz.f32 %0, %1;" : "=f"(r) : "f"(x)); return r; }
__device__ __forceinline__ float rcp(float x) { float r; asm("rcp.approx.ftz.f32 %0, %1;" : "=f"(r) : "f"(x)); return r; }
constexpr float LOG2E = 1.4426950408889634f;
__device__ __forceinline__ float sigm(float x) { return rcp(1.f + ex2(-LOG2E * x)); }

__device__ __forceinline__ float3 layernorm3(float3 v, uint32_t scr, uint32_t scr_w, int lane) {
    float s = v.x + v.y + v.z, q = v.x * v.x + v.y * v.y + v.z * v.z;
#pragma unroll
    for (int o = 16; o > 0; o >>= 1) {
        s += __shfl_xor_sync(0xffffffffu, s, o);
        q += __shfl_xor_sync(0xffffffffu, q, o);
    }
    if (lane == 0) sts64(scr_w, __float_as_uint(s), __float_as_uint(q));
    asm volatile("bar.sync 4, 192;" ::: "memory");
    const float4 e0 = ldsf4(scr), e1 = ldsf4(scr + 16), e2 = ldsf4(scr + 32);
    const float mean = ((e0.x + e0.z) + (e1.x + e1.z) + (e2.x + e2.z)) * (1.0f / D);
    const float var = ((e0.y + e0.w) + (e1.y + e1.w) + (e2.y + e2.w)) * (1.0f / D) - mean * mean;
    const float mb = rb(mean);
    float den;
    asm("sqrt.approx.ftz.f32 %0, %1;" : "=f"(den) : "f"(rb(rb(fmaxf(var, 0.f)) + 1e-5f)));
    const float inv = rcp(rb(den));
    return make_float3(rb(rb(v.x - mb) * inv), rb(rb(v.y - mb) * inv), rb(rb(v.z - mb) * inv));
}

template <int NT>
__device__ __forceinline__ void strip_load(uint32_t p4, uint32_t p2, int x, uint32_t (&b)[NT][6]) {
#pragma unroll
    for (int n = 0; n < NT; n++) {
        ldsm4t(p4 + ((n ^ x) << 4), &b[n][0]);
        ldsm2t(p2 + ((n ^ x) << 4), &b[n][4]);
    }
}
__device__ __forceinline__ float red_sum(uint32_t red_r) {
    cbar();
    float v[NCW];
#pragma unroll
    for (int w = 0; w < NCW; w++) v[w] = ldsf(red_r + w * 160);
    return ((v[0] + v[1]) + (v[2] + v[3])) + ((v[4] + v[5]) + (v[6] + v[7])) + ((v[8] + v[9]) + (v[10] + v[11]));
}
template <int NT>
__device__ __forceinline__ void strip_mma_store(const uint32_t (&a)[6], const uint32_t (&b)[NT][6], uint32_t red_w, int lane) {
    float c[NT][4];
#pragma unroll
    for (int n = 0; n < NT; n++) c[n][0] = c[n][1] = c[n][2] = c[n][3] = 0.f;
#pragma unroll
    for (int k = 0; k < 3; k++)
#pragma unroll
        for (int n = 0; n < NT; n++) mma16(c[n], a[2 * k], a[2 * k], a[2 * k + 1], a[2 * k + 1], b[n][2 * k], b[n][2 * k + 1]);
    if (lane < 4) {
#pragma unroll
        for (int n = 0; n < NT; n++) sts64(red_w + n * 32, __float_as_uint(c[n][0]), __float_as_uint(c[n][1]));
    }
}
template <int NT>
__device__ __forceinline__ float strip_mma(const uint32_t (&a)[6], const uint32_t (&b)[NT][6], uint32_t red_w, uint32_t red_r, int lane) {
    strip_mma_store<NT>(a, b, red_w, lane);
    return red_sum(red_r);
}

template <int N>
__device__ __forceinline__ void poll_slots(const uint4* p, uint32_t tag, uint4 (&v)[N]) {
    uint32_t pend = (1u << N) - 1;
    unsigned n = 0;
    bool more;
#pragma unroll 1
    do {
#pragma unroll
        for (int i = 0; i < N; i++) if (pend & (1u << i)) v[i] = ld_msg(p + i * 32);
        uint32_t x = 0;
#pragma unroll
        for (int i = 0; i < N; i++) x |= v[i].w ^ tag;
        more = __any_sync(0xffffffffu, x != 0);
        if (!more) break;
        pend = 0;
#pragma unroll
        for (int i = 0; i < N; i++) pend |= v[i].w != tag ? 1u << i : 0u;
    } while (++n < SPIN_MAX);
}
__device__ __forceinline__ float reduce_part(const uint4* p, uint32_t tag, int lane) {
    uint4 v[8];
    poll_slots<8>(p, tag, v);
#define F(i, c) __uint_as_float(v[i].c)
    float s0 = ((F(0, x) + F(1, x)) + (F(2, x) + F(3, x))) + ((F(4, x) + F(5, x)) + (F(6, x) + F(7, x)));
    float s1 = ((F(0, y) + F(1, y)) + (F(2, y) + F(3, y))) + ((F(4, y) + F(5, y)) + (F(6, y) + F(7, y)));
    float s2 = ((F(0, z) + F(1, z)) + (F(2, z) + F(3, z))) + ((F(4, z) + F(5, z)) + (F(6, z) + F(7, z)));
#undef F
#pragma unroll
    for (int o = 16; o > 1; o >>= 1) {
        s0 += __shfl_xor_sync(0xffffffffu, s0, o);
        s1 += __shfl_xor_sync(0xffffffffu, s1, o);
        s2 += __shfl_xor_sync(0xffffffffu, s2, o);
    }
    return lane < 2 ? s0 : lane < 4 ? s1 : s2;
}

struct Params {
    uint32_t sched[NPOS];
    uint32_t stagger;
    uint32_t probe_deadline;
    const __nv_bfloat16* b2;
    CUtensorMap m_wq, m_k, m_v, m_wo, m_w1, m_w2, m_w1x;
};

__global__ void __launch_bounds__(NTHREADS, 1)
fused_kernel(const __nv_bfloat16* __restrict__ p_wmod, const __nv_bfloat16* __restrict__ p_c, const __nv_bfloat16* __restrict__ p_x,
             uint4* const box, const __nv_bfloat16* __restrict__ p_b1, __nv_bfloat16* __restrict__ p_out,
             const __grid_constant__ Params P) {
    extern __shared__ __align__(1024) unsigned char smem[];
    uint32_t t_start;
    asm volatile("mov.u32 %0, %globaltimer_lo;" : "=r"(t_start));
    uint32_t tid = threadIdx.x, warp = tid >> 5, lane = tid & 31;
    uint32_t cta = blockIdx.x;
    const uint32_t sb = smem_u32(smem);
#define BAR(i) (sb + SM_BAR + (i) * 8)
    if (warp < NCW && cta < NMOD) {
        const uint32_t row = warp * 48 + (lane >> 2);
        const char* src = reinterpret_cast<const char*>(p_wmod) + (row * (6 * D * 2) + cta * 64 + (lane & 3) * 16);
        const uint32_t d = sb + SM_M + row * 64 + (((lane & 3) ^ ((lane >> 3) & 3)) << 4);
#pragma unroll
        for (int k = 0; k < 6; k++) cp16(d + k * 512, src + k * 8 * (6 * D * 2));
    }
    uint32_t grp = cta >> 3, rk = cta & 7;

    if (warp == NCW) {
        const uint32_t sc = P.sched[min(lane, NPOS - 1u)], stagger = P.stagger;
        const int i = sc & 63;
        int mapi = 1, c0 = 0, c1, bytes = 16384, fbar = -1;
        uint32_t dst;
        if (i < IT_K) {
            mapi = 0; c0 = cta * 32; c1 = (i - IT_WQ) * 192; dst = SM_WQ + (i - IT_WQ) * 12288; bytes = 12288;
        } else if (i < IT_WO) {
            const int k = (i - IT_K) & 7;
            c1 = (grp * SK + (SK - WIN) + ((k >> 1) * 16 + rk * 2 + (k & 1)) * 64) * 2;
            dst = SM_K + k * 16384;
            if (i >= IT_V) {
                mapi = 2; dst = SM_RING + (k < 5 ? k : k - 5) * 16384;
                fbar = k == 0 ? BF_WQ : k >= 5 ? BF_V0 + k - 5 : -1;
            }
        } else if (i < IT_W2) {
            mapi = 3; c1 = (grp * 256 + (i - IT_WO) * 128 + rk * 16) * 9; dst = SM_WO + (i - IT_WO) * 18432; bytes = 18432;
            fbar = BF_K;
        } else if (i < IT_W1) {
            mapi = 5; c1 = (cta * 32 + (i - IT_W2) * 16) * 9; dst = SM_W2 + (i - IT_W2) * 18432; bytes = 18432;
        } else if (i < IT_W2C) {
            mapi = 4; c0 = cta * 32; c1 = (i - IT_W1) * 192; dst = SM_W1 + (i - IT_W1) * 12288; bytes = 12288;
        } else if (i == IT_W2C) {
            mapi = 5; c1 = (4096 + (cta - NRED) * 16) * 9; dst = SM_W2 + 2 * 18432; bytes = cta >= NRED ? 18432 : 0;
        } else {
            mapi = 6; c0 = 4096 + (cta - NRED) * 16; c1 = 0; dst = SM_W1X; bytes = cta >= NRED ? 18432 : 0;
            fbar = BF_X;
        }
        uint64_t pol;
        asm volatile("createpolicy.fractional.L2::evict_first.b64 %0, 1.0;" : "=l"(pol));
        const uint32_t t_iss = t_start + (sc >> 16) + ((((sc >> 12) & 15) * ((cta + 32) & 127) * stagger) >> 10);
        const CUtensorMap* map = &P.m_wq + mapi;
        const uint32_t gates = ((sc >> 6) & 63) | ((uint32_t)(fbar & 63) << 8);
        asm volatile("bar.sync 2, %0;" ::"n"(NTHREADS) : "memory");
#pragma unroll 1
        for (int k = cta >= NMOD ? 3 : 0; k < NPOS; k++) {
            const uint32_t gk = __shfl_sync(0xffffffffu, gates, k);
            const uint32_t tk = __shfl_sync(0xffffffffu, t_iss, k);
            if ((gk & 63) != IT_NONE) mbar_wait(BAR(gk & 63));
            if ((gk >> 8) != IT_NONE) mbar_wait(BAR(gk >> 8));
            uint32_t now;
            unsigned n = 0;
            do { asm volatile("mov.u32 %0, %globaltimer_lo;" : "=r"(now)); } while ((int)(now - tk) < 0 && ++n < SPIN_MAX);
            if (lane == k && bytes) {
                const uint32_t bk = BAR(i);
                mbar_expect_tx(bk, bytes);
                tma2d(sb + dst, map, c0, c1, bk, pol);
                if (mapi == 6) { tma2d(sb + dst + 6144, map, c0, 192, bk, pol); tma2d(sb + dst + 12288, map, c0, 384, bk, pol); }
            }
            __syncwarp();
        }
        return;
    }

    if (warp > NCW) {
        if (lane == 0) {
#pragma unroll
            for (int i = 0; i < NBAR_USED; i++) mbar_init(BAR(i), i == IT_M ? NCT : i >= BF_X ? 4 : 1);
            asm volatile("fence.mbarrier_init.release.cluster;" ::: "memory");
        }
        __syncwarp();
        asm volatile("bar.arrive 2, %0;" ::"n"(NTHREADS) : "memory");
        if (lane == 0 && cta >= NMOD) {
            uint64_t pol;
            asm volatile("createpolicy.fractional.L2::evict_first.b64 %0, 1.0;" : "=l"(pol));
#pragma unroll
            for (int i = 0; i < 3; i++) {
                mbar_expect_tx(BAR(IT_WQ + i), 12288);
                tma2d(sb + SM_WQ + i * 12288, &P.m_wq, cta * 32, i * 192, BAR(IT_WQ + i), pol);
            }
        }
        __syncwarp();
        st_msg(box + half_of(BX_O + cta * 512, (lane >> 1) & 1) + 128 + (lane >> 2) * 16 + (lane & 1), 0u, 0u, 0u, 0u);
        uint32_t epoch;
        asm volatile("ld.relaxed.gpu.global.u32 %0, [%1];" : "=r"(epoch) : "l"(box + BX_EPOCH) : "memory");
        if (lane < 7) asm volatile("prefetch.tensormap [%0];" ::"l"(&P.m_wq + lane) : "memory");
        lane = __shfl_sync(0xffffffffu, lane, lane); cta = __shfl_sync(0xffffffffu, cta, 0);
        if (lane == 0) {
            uint32_t best0 = 0xffffffffu, best1 = 0xffffffffu, prev = 0;
            int wins = 0;
            bool clear = false;
#pragma unroll 1
            for (uint32_t r = 0; r < 80; r++) {
                uint32_t c0, c1 = 0;
                asm volatile("{\n.reg .pred p;\n.reg .u32 v;\nmov.u32 %0, %clock;\natom.relaxed.gpu.global.exch.b32 v, [%2], 0;\n"
                             "setp.ne.u32 p, v, 1;\n@p mov.u32 %1, %clock;\n}" : "=r"(c0), "+r"(c1)
                             : "l"(box + half_of(BX_O + cta * 512, r & 1) + 128 + ((r >> 1) & 7) * 16) : "memory");
                const uint32_t d = c1 - c0;
                if (r & 1) best1 = min(best1, d); else best0 = min(best0, d);
                if (r >= 3) wins += ((d < prev) == (r & 1)) ? 1 : -1;
                prev = d;
                const uint32_t lo = min(best0, best1), hi = max(best0, best1);
                clear = lo < 380 && lo * 10 < hi * 8;
                uint32_t now;
                asm volatile("mov.u32 %0, %globaltimer_lo;" : "=r"(now));
                if (r >= 3 && (clear || now - t_start > P.probe_deadline)) break;
            }
            uint32_t smid;
            asm volatile("mov.u32 %0, %smid;" : "=r"(smid));
            const uint32_t side = (clear || wins == 0) ? best1 < best0 : wins > 0;
            asm volatile("st.relaxed.gpu.global.u32 [%0], %1;" ::"l"(reinterpret_cast<uint32_t*>(box + BX_SIDE) + cta),
                         "r"(((epoch * 2 + 1) << 16) | ((smid >> 1) << 2) | (clear ? 2u : 0u) | side) : "memory");
        }
        __syncwarp();
        const uint32_t tag = epoch * 2 + 1;
        const uint32_t rcol = min(48 * (cta >> 3) + 8 * min(lane, 5u) + (cta & 7), D - 1u);
        const uint32_t rx = ldg16(p_x + rcol), rb2 = ldg16(P.b2 + rcol);
        const uint32_t rb1 = ldg16(p_b1 + cta * 32 + lane), rb1x = ldg16(p_b1 + 4096 + (cta & 31) * 16 + (lane & 15));
        __nv_bfloat16* const op = p_out + rcol;
        uint2* const x2_dst = reinterpret_cast<uint2*>(box + half_of(BX_X2 + ((lane >> 3) & 1) * 512, lane >> 1) + ((lane >> 2) & 1) * 128) +
                              (cta * 2 + (lane & 1));
        if (cta < NRED && lane < 16) st_msg8(x2_dst, 0u, 0u);
        mbar_wait(BAR(IT_K + 4));
        float ga, gb;
        {
            const uint4 va = poll_msg<200>(box + BX_MOD + (2 * D + rcol) / 4, tag), vb = poll_msg<200>(box + BX_MOD + (5 * D + rcol) / 4, tag);
            const uint32_t ua = rcol & 2 ? va.y : va.x, ub = rcol & 2 ? vb.y : vb.x;
            ga = rcol & 1 ? bhi(ua) : blo(ua);
            gb = rcol & 1 ? bhi(ub) : blo(ub);
        }
        asm volatile("bar.sync 3, %0;" ::"n"(NCT + 32) : "memory");
        const uint32_t side = lds32(sb + SM_XN + cta * 4);
        const uint4* part_src = box + (half_of(BX_PART + min(cta, NRED - 1u) * 512, side) + lane);
        {
            const uint4* src = box + (half_of(BX_O + cta * 512, side) + lane);
            mbar_wait(BAR(IT_V + 7));
            uint4 v[4];
            poll_slots<4>(src, tag, v);
            float o0 = (__uint_as_float(v[0].x) + __uint_as_float(v[1].x)) + (__uint_as_float(v[2].x) + __uint_as_float(v[3].x));
            float o1 = (__uint_as_float(v[0].y) + __uint_as_float(v[1].y)) + (__uint_as_float(v[2].y) + __uint_as_float(v[3].y));
            const float o = (lane < 16 ? o0 : o1) + __shfl_xor_sync(0xffffffffu, lane < 16 ? o1 : o0, 16);
            sts16(sb + SM_O + lane * 2, f2b(o));
            asm volatile("bar.arrive 10, %0;" ::"n"(NCT + 32) : "memory");
        }
        float r_x2 = 0.f;
        if (cta < NRED) {
            mbar_wait(BAR(IT_WO + 1));
            const float sv = reduce_part(part_src, tag, lane);
            r_x2 = rb(blo(rx) + rb(ga * rb(sv)));
            const uint32_t w = __float_as_uint(r_x2);
            const uint32_t w0 = __shfl_sync(0xffffffffu, w, lane & 1), w1 = __shfl_sync(0xffffffffu, w, (lane & 1) + 2),
                           w2 = __shfl_sync(0xffffffffu, w, (lane & 1) + 4);
            if (lane < 16) st_msg8(x2_dst, (w0 >> 16) | w1, (w2 >> 16) | (tag << 16));
            __syncwarp();
            asm volatile("bar.arrive 9, 224;" ::: "memory");
        }
        {
            asm volatile("bar.sync 8, %0;" ::"n"(NCT + 32) : "memory");
            uint32_t hv[2];
#pragma unroll
            for (int k = 0; k < 2; k++) {
                const uint32_t ra = sb + SM_RED + (k ? 32 + (lane & 15) : lane) * 48;
                const float4 p0 = ldsf4(ra), p1 = ldsf4(ra + 16), p2 = ldsf4(ra + 32);
                const float r = ((p0.x + p0.y) + (p0.z + p0.w)) + ((p1.x + p1.y) + (p1.z + p1.w)) + ((p2.x + p2.y) + (p2.z + p2.w));
                const float u = rb(rb(r) + blo(k ? rb1x : rb1));
                const float z = 1.5957691216057308f * (u + 0.044715f * u * u * u);
                hv[k] = f2b(u * sigm(z));
            }
            sts16(sb + SM_O + lane * 2, hv[0]);
            if (lane < 16) sts16(sb + SM_O + 64 + lane * 2, hv[1]);
            __syncwarp();
            asm volatile("bar.arrive 6, %0;" ::"n"(NCT + 32) : "memory");
        }
        if (cta < NRED) {
            mbar_wait(BAR(IT_W2 + 1));
            const float sv = reduce_part(part_src, tag + 1, lane);
            const uint32_t y = f2b(r_x2 + rb(gb * rb(rb(sv) + blo(rb2))));
            if (lane < 6) asm volatile("st.global.u16 [%0], %1;" ::"l"(op), "r"(y) : "memory");
            if (cta == 0 && lane == 0) asm volatile("st.relaxed.gpu.global.u32 [%0], %1;" ::"l"(box + BX_EPOCH), "r"(epoch + 1) : "memory");
        }
        return;
    }

    tid = __shfl_sync(0xffffffffu, tid, lane); cta = __shfl_sync(0xffffffffu, cta, 0);
    warp = tid >> 5; lane = tid & 31; grp = cta >> 3; rk = cta & 7;
    const uint32_t t = lane & 3, gq = lane >> 2;
    const uint32_t li = tid - 64;
    const bool is_ln = li < 192;
    const uint32_t lcol = is_ln ? 48 * (li >> 4) + 8 * (li & 1) + ((li >> 1) & 7) : 0;
    const uint32_t vi = warp * 24 + min(lane, 23u);
    uint32_t cv, epoch, x0, x1, x2;
    asm volatile("ld.global.nc.u32 %0, [%1];" : "=r"(cv) : "l"(reinterpret_cast<const uint32_t*>(p_c) + vi));
    asm volatile("ld.relaxed.gpu.global.u32 %0, [%1];" : "=r"(epoch) : "l"(box + BX_EPOCH) : "memory");
    x0 = ldg16(p_x + lcol); x1 = ldg16(p_x + lcol + 16); x2 = ldg16(p_x + lcol + 32);
    asm volatile("cp.async.commit_group;" ::: "memory");
    asm volatile("bar.sync 2, %0;" ::"n"(NTHREADS) : "memory");
    cp_arrive(BAR(IT_M));
    if (warp == 8) {
        const uint32_t idx = lane < 8 ? BX_MOD + cta * 8 + lane : lane < 16 ? BX_Q + cta * 8 + lane - 8 : BX_ML + cta * 2 + lane - 16;
        if (lane < 18 && (lane >= 8 || cta < NMOD)) st_msg(box + idx, 0u, 0u, 0u, 0u);
    }
    uint32_t a[6];
    {
        PIN(cv);
        const float c0 = blo(cv), c1 = bhi(cv);
        const uint32_t av = pack2(c0 * sigm(c0), c1 * sigm(c1));
#pragma unroll
        for (int i = 0; i < 6; i++) a[i] = __shfl_sync(0xffffffffu, av, i * 4 + t);
    }
    const uint32_t scr_w = sb + SM_SMALL + (warp - 2) * 8;
    PIN(x0); PIN(x1); PIN(x2);
    if (is_ln) {
        const float3 xv = layernorm3(make_float3(blo(x0), blo(x1), blo(x2)), sb + SM_SMALL + 192, scr_w + 192, lane);
        sts16(sb + SM_XN + lcol * 2, __float_as_uint(xv.x) >> 16);
        sts16(sb + SM_XN + lcol * 2 + 32, __float_as_uint(xv.y) >> 16);
        sts16(sb + SM_XN + lcol * 2 + 64, __float_as_uint(xv.z) >> 16);
    }
    const uint32_t tag = epoch * 2 + 1, tag2 = epoch * 2 + 2;
    const uint32_t red_w = sb + SM_RED + warp * 160 + lane * 8, red_r = sb + SM_RED + min(tid, 39u) * 4;
    const uint32_t r4 = warp * 48 + lane, r2 = warp * 48 + 32 + (lane & 15);

    asm volatile("cp.async.wait_group 0;" ::: "memory");
    asm volatile("fence.proxy.async.shared::cta;" ::: "memory");
    __syncwarp();
    const bool extra = cta >= NRED;
    const uint32_t w1row = warp * 48 + (lane & 7) + 8 * (lane >> 4);
#pragma unroll 1
    for (uint32_t ph = cta < NMOD ? 0 : 1; ph < 2; ph++) {
        if (ph) {
            cbar();
            const uint32_t l24 = min(lane, 23u), sl = (l24 >= 12 ? 132 : 0) + warp * 12 + l24;
            mbar_wait(BAR(IT_WQ + 1));
            const uint4 v = poll_msg<250>(box + BX_MOD + sl, tag);
            sts64(sb + SM_MOD + sl * 8, v.x, v.y);
            __syncwarp();
            const uint32_t xn = lds32(sb + SM_XN + vi * 4), sa = lds32(sb + SM_MOD + vi * 4), ca = lds32(sb + SM_MOD + 1152 + vi * 4);
            const uint32_t one = pack2(1.f + blo(ca), 1.f + bhi(ca));
            const uint32_t pr = pack2(blo(xn) * blo(one), bhi(xn) * bhi(one));
            const uint32_t av = pack2(blo(pr) + blo(sa), bhi(pr) + bhi(sa));
#pragma unroll
            for (int i = 0; i < 6; i++) a[i] = __shfl_sync(0xffffffffu, av, i * 4 + t);
            mbar_wait(BAR(IT_WQ + (warp >> 2)));
        }
        uint32_t b[4][6];
        strip_load<4>(sb + SM_M + ph * 36864 + r4 * 64, sb + SM_M + ph * 36864 + r2 * 64, (lane >> 1) & 3, b);
        const float r = strip_mma<4>(a, b, red_w, red_r, lane);
        if (warp == 0) {
            sts16(sb + SM_O + lane * 2, f2b(r));
            __syncwarp();
            if (lane < 8) st_msg(box + (ph ? BX_Q : BX_MOD) + cta * 8 + lane, lds32(sb + SM_O + lane * 8), lds32(sb + SM_O + lane * 8 + 4), 0u, tag);
        }
    }
    if (tid == 0) mbar_arrive(BAR(BF_WQ));
    if (li < 64) {
        const uint4 v = poll_msg<200>(box + BX_Q + grp * 64 + li, tag);
        sts64(sb + SM_Q + li * 8, v.x, v.y);
    }
    cbar();
    const uint32_t ob = sb + SM_O + t * 4;

    if (warp < 8) {
        uint32_t bq[4][2];
        const uint32_t msk = gq < 4 ? 0xffffffffu : 0u;
#pragma unroll
        for (int ks = 0; ks < 4; ks++) {
            const uint32_t qa = sb + SM_Q + ((gq & 1) * 64 + (gq & 2) * 16 + ks * 8 + t) * 4;
            bq[ks][0] = lds32(qa) & msk;
            bq[ks][1] = lds32(qa + 16) & msk;
        }
        float mx0 = -INFINITY, mx1 = -INFINITY;
        uint32_t rowaddr = sb + SM_K + (warp * 16 + (lane & 15)) * 128;
        const uint32_t xo = (lane >> 4) ^ (lane & 7);
        uint32_t sa = sb + SM_S + (warp * 8 + (lane >> 3)) * 4;
#pragma unroll 1
        for (int ch = 0; ch < 8; ch += 2) {
            uint32_t ka[2][4][4];
#pragma unroll
            for (int u = 0; u < 2; u++) {
                mbar_wait(BAR(IT_K + ch + u));
#pragma unroll
                for (int ks = 0; ks < 4; ks++) ldsm4(rowaddr + u * 16384 + (((2 * ks) ^ xo) << 4), ka[u][ks]);
            }
            float c[2][4];
#pragma unroll
            for (int u = 0; u < 2; u++) c[u][0] = c[u][1] = c[u][2] = c[u][3] = 0.f;
#pragma unroll
            for (int ks = 0; ks < 4; ks++)
#pragma unroll
                for (int u = 0; u < 2; u++)
                    mma16(c[u], ka[u][ks][0], ka[u][ks][1], ka[u][ks][2], ka[u][ks][3], bq[ks][0], bq[ks][1]);
            const float sc = 0.08838834764831845f;
#pragma unroll
            for (int u = 0; u < 2; u++) {
#pragma unroll
                for (int i = 0; i < 4; i++) c[u][i] = rb(rb(c[u][i] + __shfl_down_sync(0xffffffffu, c[u][i], 5)) * sc);
                if ((lane & 7) == 0) {
                    const uint32_t d = sa + u * 256;
                    stsf(d, c[u][0]); stsf(d + 2048, c[u][1]); stsf(d + 16, c[u][2]); stsf(d + 2064, c[u][3]);
                }
                mx0 = fmaxf(mx0, fmaxf(c[u][0], c[u][2]));
                mx1 = fmaxf(mx1, fmaxf(c[u][1], c[u][3]));
            }
            rowaddr += 32768; sa += 512;
        }
#pragma unroll
        for (int o = 8; o <= 16; o <<= 1) {
            mx0 = fmaxf(mx0, __shfl_xor_sync(0xffffffffu, mx0, o));
            mx1 = fmaxf(mx1, __shfl_xor_sync(0xffffffffu, mx1, o));
        }
        if (lane == 0) { stsf(sb + SM_SMALL + warp * 4, mx0); stsf(sb + SM_SMALL + 32 + warp * 4, mx1); }
        asm volatile("bar.sync 5, 256;" ::: "memory");
        if (tid == 0) mbar_arrive(BAR(BF_K));
        const uint32_t hd = warp >> 2;
        const float4 ma = ldsf4(sb + SM_SMALL + hd * 32), mb = ldsf4(sb + SM_SMALL + hd * 32 + 16);
        const float4 s4 = ldsf4(sb + SM_S + tid * 16);
        const float m = fmaxf(fmaxf(fmaxf(ma.x, ma.y), fmaxf(ma.z, ma.w)), fmaxf(fmaxf(mb.x, mb.y), fmaxf(mb.z, mb.w)));
        const float p0 = ex2((s4.x - m) * LOG2E), p1 = ex2((s4.y - m) * LOG2E), p2 = ex2((s4.z - m) * LOG2E), p3 = ex2((s4.w - m) * LOG2E);
        sts64(sb + SM_P + tid * 8, pack2(p0, p1), pack2(p2, p3));
        float l = (p0 + p1) + (p2 + p3);
#pragma unroll
        for (int o = 16; o > 0; o >>= 1) l += __shfl_xor_sync(0xffffffffu, l, o);
        if (lane == 0) { stsf(sb + SM_SMALL + 128 + warp * 4, l); stsf(sb + SM_SMALL + 160 + hd * 4, m); }
        asm volatile("bar.sync 5, 256;" ::: "memory");
    }

    uint32_t wad[3];
#pragma unroll
    for (int i = 0; i < 3; i++) {
        const uint32_t T = warp * 3 + i, blk = T >> 2, ch = 2 * (T & 3) + ((lane >> 3) & 1);
        const uint32_t fr = ((lane & 7) + 8 * (lane >> 4)) * 9 + blk;
        wad[i] = sb + fr * 128 + ((ch ^ (fr & 7)) << 4);
        PIN(wad[i]);
    }
    if (warp < 4) {
        float c[2][4];
#pragma unroll
        for (int i = 0; i < 2; i++) c[i][0] = c[i][1] = c[i][2] = c[i][3] = 0.f;
        const uint32_t row = (lane & 7) + 8 * (lane >> 4);
        const uint32_t off = sb + SM_RING + row * 128 + (((2 * warp + ((lane >> 3) & 1)) ^ (lane & 7)) << 4);
        uint32_t pp = sb + SM_P + ((gq & 1) * 512 + t) * 2;
        const uint32_t mul = gq < 2 ? 1u : gq < 4 ? 65536u : 0u;
        float f0 = 0.f, f1 = 0.f;
        uint4* o_dst = box;
        uint32_t slot = 0;
#pragma unroll 1
        for (int ch = 0; ch < 8; ch++) {
            uint32_t bp[16];
#pragma unroll
            for (int i = 0; i < 16; i++) bp[i] = lds16(pp + i * 8) * mul;
            if (ch == 7) {
                asm volatile("bar.sync 3, %0;" ::"n"(NCT + 32) : "memory");
                f0 = ldsf(sb + SM_SMALL + 176); f1 = ldsf(sb + SM_SMALL + 180);
                const uint32_t ro = grp * 8 + (t & 1) * 4 + warp;
                o_dst = box + (half_of(BX_O + ro * 512, lds32(sb + SM_XN + ro * 4)) + rk * 16 + gq);
            }
            uint32_t base = off + slot * 16384;
            PIN(base);
            mbar_wait(BAR(IT_V + ch));
            uint32_t va[8][4];
#pragma unroll
            for (int ks = 0; ks < 8; ks++) ldsm4t(base + ks * 2048, va[ks]);
#pragma unroll
            for (int ks = 0; ks < 8; ks++) mma16(c[ks & 1], va[ks][0], va[ks][1], va[ks][2], va[ks][3], bp[2 * ks], bp[2 * ks + 1]);
            if ((ch < 3 || ch == 4) && lane == 0) mbar_arrive(BAR(ch == 4 ? BF_X : BF_V0 + ch));
            slot = slot == 4 ? 0 : slot + 1;
            pp += 128;
        }
        if (t < 2) {
            st_msg(o_dst, __float_as_uint((c[0][0] + c[1][0]) * f0), __float_as_uint((c[0][1] + c[1][1]) * f1), 0u, tag);
            st_msg(o_dst + 8, __float_as_uint((c[0][2] + c[1][2]) * f0), __float_as_uint((c[0][3] + c[1][3]) * f1), 0u, tag);
        }
    } else {
        if (warp == 4) {
            const uint32_t hd = lane & 1;
            const float m_own = ldsf(sb + SM_SMALL + 160 + hd * 4);
            const float4 l4 = ldsf4(sb + SM_SMALL + 128 + hd * 16);
            if (lane < 2) st_msg(box + BX_ML + cta * 2 + lane, __float_as_uint(m_own), __float_as_uint((l4.x + l4.y) + (l4.z + l4.w)), 0u, tag);
            mbar_wait(BAR(IT_V + 3));
            const uint4 v = poll_msg<300>(box + BX_ML + grp * 16 + (lane & 15), tag);
            const float ms = __uint_as_float(v.x);
            float M = ms;
#pragma unroll
            for (int o = 2; o <= 8; o <<= 1) M = fmaxf(M, __shfl_xor_sync(0xffffffffu, M, o));
            float L = __uint_as_float(v.y) * ex2((ms - M) * LOG2E);
#pragma unroll
            for (int o = 2; o <= 8; o <<= 1) L += __shfl_xor_sync(0xffffffffu, L, o);
            if (lane < 2) stsf(sb + SM_SMALL + 176 + lane * 4, ex2((m_own - M) * LOG2E) * rcp(L));
        } else if (warp >= 8) {
#pragma unroll 1
            for (uint32_t i = tid - 256; i < 288; i += 128) {
                const uint4 v = poll_msg<200>(box + BX_MOD + 432 + i, tag);
                sts64(sb + SM_MOD + i * 8, v.x, v.y);
            }
            mbar_wait(BAR(IT_V + 2));
            const uint32_t u = tid - 256;
            const uint32_t* side = reinterpret_cast<const uint32_t*>(box + BX_SIDE) + u;
            uint32_t sp;
            unsigned n = 0;
#pragma unroll 1
            do {
                if (n) __nanosleep(500);
                asm volatile("ld.relaxed.gpu.global.u32 %0, [%1];" : "=r"(sp) : "l"(side) : "memory");
            } while (__any_sync(0xffffffffu, (sp >> 16) != (tag & 0xffffu)) && ++n < SPIN_MAX);
            const uint32_t nb = __shfl_xor_sync(0xffffffffu, sp, 1);
            sts32(sb + SM_XN + u * 4, (((sp ^ nb) >> 1) == 1 && (nb & 2) ? nb : sp) & 1);
            asm volatile("bar.sync 7, 128;" ::: "memory");
#pragma unroll
            for (int k = 0; k < 2; k++) {
                const uint32_t rp = k * 64 + (u >> 1);
                if (rp < NRED) st_msg(box + (half_of(BX_PART + rp * 512, lds32(sb + SM_XN + rp * 4)) + cta * 2 + (u & 1)), 0u, 0u, 0u, 0u);
            }
            const uint32_t ro = grp * 8 + (u >> 4);
            st_msg(box + (half_of(BX_O + ro * 512, lds32(sb + SM_XN + ro * 4)) + rk * 16 + (u & 15)), 0u, 0u, 0u, 0u);
            asm volatile("bar.arrive 3, %0;" ::"n"(NCT + 32) : "memory");
        }
        if (warp < 8) asm volatile("bar.sync 3, %0;" ::"n"(NCT + 32) : "memory");
    }

    uint4* const part_dst = box + (half_of(BX_PART + (warp * 8 + gq) * 512, lds32(sb + SM_XN + (warp * 8 + gq) * 4)) + cta * 2 + (t & 1));
    const uint32_t my_side = lds32(sb + SM_XN + cta * 4);
    {
        uint32_t wa[3][8];
        mbar_wait(BAR(IT_WO));
#pragma unroll
        for (int i = 0; i < 3; i++) ldsm4t(wad[i] + SM_WO, &wa[i][0]);
        const bool pre0 = mbar_test(BAR(IT_WO + 1));
        if (pre0) {
#pragma unroll
            for (int i = 0; i < 3; i++) ldsm4t(wad[i] + SM_WO + 16 * 1152, &wa[i][4]);
        }
        asm volatile("bar.sync 10, %0;" ::"n"(NCT + 32) : "memory");
        const uint32_t b0 = lds32(ob), b1 = lds32(ob + 16), b2 = lds32(ob + 32), b3 = lds32(ob + 48);
        float c[3][4];
#pragma unroll
        for (int i = 0; i < 3; i++) {
            c[i][0] = c[i][1] = c[i][2] = c[i][3] = 0.f;
            mma16(c[i], wa[i][0], wa[i][1], wa[i][2], wa[i][3], b0, b1);
        }
        if (!pre0) {
            mbar_wait(BAR(IT_WO + 1));
#pragma unroll
            for (int i = 0; i < 3; i++) ldsm4t(wad[i] + SM_WO + 16 * 1152, &wa[i][4]);
        }
#pragma unroll
        for (int i = 0; i < 3; i++) mma16(c[i], wa[i][4], wa[i][5], wa[i][6], wa[i][7], b2, b3);
        if (t < 2) st_msg(part_dst, __float_as_uint(t ? c[0][2] : c[0][0]), __float_as_uint(t ? c[1][2] : c[1][0]),
                          __float_as_uint(t ? c[2][2] : c[2][0]), tag);
    }
    uint32_t wb[6][4], wx[3][4];
    const uint32_t w1bar = BAR((lane & 1) && extra ? IT_W1X : IT_W1 + (warp >> 2));
    const uint32_t w1a = sb + SM_W1 + w1row * 64 + ((((lane >> 3) & 1) ^ ((lane >> 1) & 3)) << 4);
    const uint32_t w1x = sb + SM_W1X + w1row * 32 + ((lane >> 3) & 1) * 16;
#define W1_LOAD() do { _Pragma("unroll") for (int k = 0; k < 3; k++) { \
        if (extra) ldsm4t(w1x + k * 512, wx[k]); \
        ldsm4t(w1a + k * 1024, wb[k * 2]); ldsm4t((w1a ^ 32) + k * 1024, wb[k * 2 + 1]); } } while (0)
    bool pre1 = false;
    if (is_ln) {
        const uint32_t ma = sb + SM_MOD + lcol * 2;
        float c0 = rb(1.f + blo(lds16(ma + 2 * D))), c1 = rb(1.f + blo(lds16(ma + 2 * D + 32))), c2 = rb(1.f + blo(lds16(ma + 2 * D + 64)));
        float s0 = blo(lds16(ma)), s1 = blo(lds16(ma + 32)), s2 = blo(lds16(ma + 64));
        const uint2* src = reinterpret_cast<const uint2*>(box + half_of(BX_X2 + (cta & 2) * 256, my_side) + (cta & 1) * 128) + li;
        const uint32_t yd = sb + SM_VEC + lcol * 2;
        uint2 v;
        bool xp = true;
        unsigned n = 0;
        if (cta < NRED) asm volatile("bar.sync 9, 224;" ::: "memory");
        else mbar_wait(w1bar);
        pre1 = mbar_test(w1bar);
        if (pre1) W1_LOAD();
#pragma unroll 1
        do { if (xp) v = ld_msg8(src); xp = (v.y >> 16) != (tag & 0xffffu); } while (__any_sync(0xffffffffu, xp) && ++n < SPIN_MAX);
        float3 y = layernorm3(make_float3(blo(v.x), bhi(v.x), blo(v.y)), sb + SM_SMALL, scr_w, lane);
        y = layernorm3(make_float3(rb(rb(y.x * c0) + s0), rb(rb(y.y * c1) + s1), rb(rb(y.z * c2) + s2)), sb + SM_SMALL + 64, scr_w + 64, lane);
        sts16(yd, __float_as_uint(y.x) >> 16); sts16(yd + 32, __float_as_uint(y.y) >> 16); sts16(yd + 64, __float_as_uint(y.z) >> 16);
    }
    {
        const uint32_t ya = sb + SM_VEC + (warp * 24 + t) * 4;
        const uint32_t rd = sb + SM_RED + (t * 16 + gq) * 48 + warp * 4;
        if (!pre1) {
            mbar_wait(w1bar);
            __syncwarp();
            W1_LOAD();
        }
        cbar();
#pragma unroll
        for (int i = 0; i < 6; i++) a[i] = lds32(ya + i * 16);
        float c[3][4];
#pragma unroll
        for (int j = 0; j < 3; j++) c[j][0] = c[j][1] = c[j][2] = c[j][3] = 0.f;
#pragma unroll
        for (int k = 0; k < 3; k++) {
#pragma unroll
            for (int j = 0; j < 2; j++) mma16(c[j], wb[k * 2 + j][0], wb[k * 2 + j][1], wb[k * 2 + j][2], wb[k * 2 + j][3], a[2 * k], a[2 * k + 1]);
            if (extra) mma16(c[2], wx[k][0], wx[k][1], wx[k][2], wx[k][3], a[2 * k], a[2 * k + 1]);
        }
        if (t < 3) {
            stsf(rd, t == 0 ? c[0][0] : t == 1 ? c[1][0] : c[2][0]);
            stsf(rd + 8 * 48, t == 0 ? c[0][2] : t == 1 ? c[1][2] : c[2][2]);
        }
        asm volatile("bar.arrive 8, %0;" ::"n"(NCT + 32) : "memory");
    }
    {
        uint32_t wa[3][12];
        mbar_wait(BAR((lane & 1) && extra ? IT_W2C : IT_W2));
        __syncwarp();
#pragma unroll
        for (int i = 0; i < 3; i++) {
            ldsm4t(wad[i] + SM_W2, &wa[i][0]);
            if (extra) ldsm4t(wad[i] + SM_W2 + 32 * 1152, &wa[i][8]);
        }
        const bool pre = mbar_test(BAR(IT_W2 + 1));
        if (pre) {
#pragma unroll
            for (int i = 0; i < 3; i++) ldsm4t(wad[i] + SM_W2 + 16 * 1152, &wa[i][4]);
        }
        asm volatile("bar.sync 6, %0;" ::"n"(NCT + 32) : "memory");
        uint32_t b[6];
#pragma unroll
        for (int i = 0; i < 6; i++) b[i] = lds32(ob + i * 16);
        float c[3][4], e[3][4], f[3][4];
#pragma unroll
        for (int i = 0; i < 3; i++) {
#pragma unroll
            for (int j = 0; j < 4; j++) c[i][j] = e[i][j] = f[i][j] = 0.f;
            mma16(c[i], wa[i][0], wa[i][1], wa[i][2], wa[i][3], b[0], b[1]);
            if (extra) mma16(e[i], wa[i][8], wa[i][9], wa[i][10], wa[i][11], b[4], b[5]);
        }
        if (!pre) {
            mbar_wait(BAR(IT_W2 + 1));
#pragma unroll
            for (int i = 0; i < 3; i++) ldsm4t(wad[i] + SM_W2 + 16 * 1152, &wa[i][4]);
        }
#pragma unroll
        for (int i = 0; i < 3; i++) mma16(f[i], wa[i][4], wa[i][5], wa[i][6], wa[i][7], b[2], b[3]);
        float r[3];
#pragma unroll
        for (int i = 0; i < 3; i++) r[i] = t ? (c[i][2] + e[i][2]) + f[i][2] : (c[i][0] + e[i][0]) + f[i][0];
        if (t < 2) st_msg(part_dst, __float_as_uint(r[0]), __float_as_uint(r[1]), __float_as_uint(r[2]), tag2);
    }
#undef BAR
}

typedef CUresult (*EncodeFn)(CUtensorMap*, CUtensorMapDataType, cuuint32_t, void*, const cuuint64_t*, const cuuint64_t*,
                             const cuuint32_t*, const cuuint32_t*, CUtensorMapInterleave, CUtensorMapSwizzle,
                             CUtensorMapL2promotion, CUtensorMapFloatOOBfill);

void make_map(EncodeFn enc, CUtensorMap* m, const void* base, uint64_t cols, uint64_t rows, uint32_t bc, uint32_t br,
              CUtensorMapSwizzle sw, CUtensorMapL2promotion promo) {
    cuuint64_t dims[2] = {cols, rows};
    cuuint64_t strides[1] = {cols * 2};
    cuuint32_t box[2] = {bc, br};
    cuuint32_t es[2] = {1, 1};
    enc(m, CU_TENSOR_MAP_DATA_TYPE_BFLOAT16, 2, const_cast<void*>(base), dims, strides, box, es,
        CU_TENSOR_MAP_INTERLEAVE_NONE, sw, promo, CU_TENSOR_MAP_FLOAT_OOB_FILL_NONE);
}

struct Tune { int t0, rate, stagger, gap, rate2, win, win2, mw; char order[40], stag[40]; };
const Tune g_tune = {-1530, 2460, 670, 220, 2600, 70, 70, 20, "abcKKKKKKKKVVVVVVVVOOxdefXYX", "8888888888888888888448888888"};
void make_schedule(Params& P, double speed) {
    const Tune& T = g_tune;
    int nk = 0, nv = 0, no = 0, nx = 0, n = 0, hist[40], hb[40], nh = 0;
    bool after = false;
    const double stagger = T.stagger / speed;
    double t = T.t0 + (T.stagger - stagger) / 2 + 31104 * 100.0 / (T.rate * speed);
    hb[nh] = T.mw * 1024; hist[nh++] = IT_M;
    for (const char* c = T.order; *c && n < NPOS; c++) {
        int item, bytes;
        switch (*c) {
            case 'a': case 'b': case 'c': item = IT_WQ + (*c - 'a'); bytes = 12288; break;
            case 'K': item = IT_K + nk++; bytes = 16384; break;
            case 'V': item = IT_V + nv++; bytes = 16384; break;
            case 'O': item = IT_WO + no++; bytes = 18432; break;
            case 'd': case 'e': case 'f': item = IT_W1 + (*c - 'd'); bytes = 12288; break;
            case 'X': item = IT_W2 + nx++; bytes = 18432; break;
            case 'x': item = IT_W1X; bytes = 4608; break;
            default: item = IT_W2C; bytes = 4608; break;
        }
        t += bytes * 100.0 / ((after ? T.rate2 : T.rate) * speed);
        int j = nh - 1, sum = bytes;
        while (j >= 0 && sum + hb[j] <= (after ? T.win2 : T.win) * 1024) sum += hb[j--];
        const int gate = j >= 0 ? hist[j] : IT_NONE;
        const int sg = T.stag[n] - '0';
        int tt = (int)(t + (8 - sg) * stagger / 16.0);
        tt = tt < 0 ? 0 : tt > 65535 ? 65535 : tt;
        P.sched[n++] = (uint32_t)item | (gate << 6) | (sg << 12) | ((uint32_t)tt << 16);
        if (bytes > 8192) { hb[nh] = bytes; hist[nh++] = item; }
        if (no == 2 && nv == 8 && !after) { after = true; t += T.gap; }
    }
    P.stagger = (uint32_t)stagger;
    P.probe_deadline = (uint32_t)(9300 / speed);
}

__device__ float f_a[FF], f_mod[6 * D], f_q[4096], f_x2[D], f_t[FF];
typedef const __nv_bfloat16* CB;
__device__ __forceinline__ float bf(CB p, size_t i) { return __bfloat162float(p[i]); }
__global__ void fb_gemv(const float* v, CB w, int K, int N, float* out) {
    const int n = blockIdx.x * blockDim.x + threadIdx.x;
    if (n >= N) return;
    float s = 0.f;
    for (int k = 0; k < K; k++) s += v[k] * bf(w, (size_t)k * N + n);
    out[n] = rb(s);
}
__device__ float fb_ln(float v, float* sh) {
    __syncthreads(); sh[threadIdx.x] = v; __syncthreads();
    float s = 0.f, q = 0.f;
    for (int i = 0; i < D; i++) s += sh[i];
    s /= D;
    for (int i = 0; i < D; i++) q += (sh[i] - s) * (sh[i] - s);
    return rb(rb(v - rb(s)) / rb(sqrtf(rb(rb(q / D) + 1e-5f))));
}
__global__ void fb_elem(int stage, CB x, CB c, CB b1, CB b2, __nv_bfloat16* out) {
    __shared__ float sh[D];
    const int i = threadIdx.x;
    if (stage == 0) { const float v = bf(c, i); f_a[i] = rb(v / (1.f + expf(-v))); }
    if (stage == 1) f_a[i] = rb(rb(fb_ln(bf(x, i), sh) * rb(1.f + f_mod[D + i])) + f_mod[i]);
    if (stage == 2) {
        f_x2[i] = rb(bf(x, i) + rb(f_mod[2 * D + i] * f_t[i]));
        f_a[i] = fb_ln(rb(rb(fb_ln(f_x2[i], sh) * rb(1.f + f_mod[4 * D + i])) + f_mod[3 * D + i]), sh);
    }
    if (stage == 3)
        for (int j = i; j < FF; j += D) {
            const float u = rb(f_t[j] + bf(b1, j));
            f_a[j] = rb(0.5f * u * (1.f + tanhf(0.7978845608028654f * (u + 0.044715f * u * u * u))));
        }
    if (stage == 4) out[i] = __float2bfloat16_rn(f_x2[i] + rb(f_mod[5 * D + i] * rb(f_t[i] + bf(b2, i))));
}
__global__ void fb_attn(CB k, CB v) {
    __shared__ float p[WIN], red[128];
    const int h = blockIdx.x, t = threadIdx.x;
    const size_t base = ((size_t)(h / 2) * SK + SK - WIN) * 128;
    float m = -INFINITY, l = 0.f, o = 0.f;
    for (int j = t; j < WIN; j += 128) {
        float s = 0.f;
        for (int d = 0; d < 128; d++) s += f_q[h * 128 + d] * bf(k, base + (size_t)j * 128 + d);
        p[j] = rb(rb(s) * 0.08838834764831845f);
        m = fmaxf(m, p[j]);
    }
    red[t] = m; __syncthreads();
    for (int i = 0; i < 128; i++) m = fmaxf(m, red[i]);
    __syncthreads();
    for (int j = t; j < WIN; j += 128) { p[j] = expf(p[j] - m); l += p[j]; }
    red[t] = l; __syncthreads();
    l = 0.f;
    for (int i = 0; i < 128; i++) l += red[i];
    for (int j = 0; j < WIN; j++) o += rb(p[j] / l) * bf(v, base + (size_t)j * 128 + t);
    f_a[h * 128 + t] = rb(o);
}
void fallback(void* const* in, void* out) {
    float *a, *mod, *q, *t;
    cudaGetSymbolAddress((void**)&a, f_a); cudaGetSymbolAddress((void**)&mod, f_mod);
    cudaGetSymbolAddress((void**)&q, f_q); cudaGetSymbolAddress((void**)&t, f_t);
#define ELEM(s) fb_elem<<<1, D>>>(s, (CB)in[0], (CB)in[10], (CB)in[7], (CB)in[9], (__nv_bfloat16*)out)
    ELEM(0); fb_gemv<<<54, 64>>>(a, (CB)in[11], D, 6 * D, mod);
    ELEM(1); fb_gemv<<<64, 64>>>(a, (CB)in[3], D, 4096, q);
    fb_attn<<<32, 128>>>((CB)in[1], (CB)in[2]); fb_gemv<<<9, 64>>>(a, (CB)in[4], 4096, D, t);
    ELEM(2); fb_gemv<<<72, 64>>>(a, (CB)in[6], D, FF, t);
    ELEM(3); fb_gemv<<<9, 64>>>(a, (CB)in[8], FF, D, t);
    ELEM(4);
#undef ELEM
}

}

extern "C" void kernel_launch(void* const* d_in, const int* in_sizes, int n_in, void* d_out, int out_size) {
    (void)in_sizes; (void)n_in; (void)out_size;
    int dev = 0, sms = 0, occ = 0, mclk = 0, bus = 0;
    cudaGetDevice(&dev);
    cudaDeviceGetAttribute(&sms, cudaDevAttrMultiProcessorCount, dev);
    cudaDeviceGetAttribute(&mclk, cudaDevAttrMemoryClockRate, dev);
    cudaDeviceGetAttribute(&bus, cudaDevAttrGlobalMemoryBusWidth, dev);
    cudaFuncSetAttribute(fused_kernel, cudaFuncAttributeMaxDynamicSharedMemorySize, SM_TOTAL);
    cudaOccupancyMaxActiveBlocksPerMultiprocessor(&occ, fused_kernel, NTHREADS, SM_TOTAL);
    void* fn = nullptr;
    cudaDriverEntryPointQueryResult qr;
    cudaGetDriverEntryPoint("cuTensorMapEncodeTiled", &fn, cudaEnableDefault, &qr);
    if (sms * occ < NATT || !fn) { (void)cudaGetLastError(); fallback(d_in, d_out); return; }
    EncodeFn enc = (EncodeFn)fn;

    Params P;
    make_map(enc, &P.m_wq, d_in[3], 4096, D, 32, 192, CU_TENSOR_MAP_SWIZZLE_64B, CU_TENSOR_MAP_L2_PROMOTION_L2_128B);
    make_map(enc, &P.m_k, d_in[1], 64, (uint64_t)HKV * SK * 2, 64, 128, CU_TENSOR_MAP_SWIZZLE_128B, CU_TENSOR_MAP_L2_PROMOTION_L2_256B);
    make_map(enc, &P.m_v, d_in[2], 64, (uint64_t)HKV * SK * 2, 64, 128, CU_TENSOR_MAP_SWIZZLE_128B, CU_TENSOR_MAP_L2_PROMOTION_L2_256B);
    make_map(enc, &P.m_wo, d_in[4], 64, 4096 * 9, 64, 144, CU_TENSOR_MAP_SWIZZLE_128B, CU_TENSOR_MAP_L2_PROMOTION_L2_256B);
    make_map(enc, &P.m_w1, d_in[6], FF, D, 32, 192, CU_TENSOR_MAP_SWIZZLE_64B, CU_TENSOR_MAP_L2_PROMOTION_L2_128B);
    make_map(enc, &P.m_w1x, d_in[6], FF, D, 16, 192, CU_TENSOR_MAP_SWIZZLE_NONE, CU_TENSOR_MAP_L2_PROMOTION_L2_64B);
    make_map(enc, &P.m_w2, d_in[8], 64, FF * 9, 64, 144, CU_TENSOR_MAP_SWIZZLE_128B, CU_TENSOR_MAP_L2_PROMOTION_L2_256B);
    P.b2 = (const __nv_bfloat16*)d_in[9];
    const double speed = mclk > 0 && bus > 0 ? (double)mclk * bus / (2619000.0 * 5120.0) : 1.0;
    make_schedule(P, speed);
    void* boxp = nullptr;
    cudaGetSymbolAddress(&boxp, g_box);
    uint4* box = (uint4*)(((uintptr_t)boxp + (2 << 20) - 1) & ~(uintptr_t)((2 << 20) - 1));
    fused_kernel<<<NATT, NTHREADS, SM_TOTAL>>>((const __nv_bfloat16*)d_in[11], (const __nv_bfloat16*)d_in[10], (const __nv_bfloat16*)d_in[0],
                                               box, (const __nv_bfloat16*)d_in[7], (__nv_bfloat16*)d_out, P);
}
```

```cpp
#include <cuda_runtime.h>
#include <cuda_bf16.h>
#include <cuda.h>
#include <stdint.h>

namespace {

constexpr int D = 576, HKV = 16, SK = 32768, WIN = 4096, FF = 4608;
constexpr int NATT = 128;
constexpr int NRED = 96;
constexpr int NMOD = 108;
constexpr int NCW = 12;
constexpr int NCT = NCW * 32;
constexpr int NTHREADS = NCT + 64;

constexpr int SM_K = 0;
constexpr int SM_WO = 0;
constexpr int SM_W2 = 36864;
constexpr int SM_W1 = 92160;
constexpr int SM_RING = 131072;
constexpr int SM_W1X = SM_RING + 3 * 16384;
constexpr int SM_M = SM_RING;
constexpr int SM_WQ = SM_RING + 36864;
constexpr int SM_MISC = SM_RING + 5 * 16384;
constexpr int SM_MOD = SM_MISC;
constexpr int SM_VEC = SM_MOD + 2304;
constexpr int SM_XN = SM_VEC + 1152;
constexpr int SM_Q = SM_XN + 1152;
constexpr int SM_S = SM_Q + 512;
constexpr int SM_P = SM_S + 4096;
constexpr int SM_RED = SM_P + 2048;
constexpr int SM_SMALL = SM_RED + 2304;
constexpr int SM_O = SM_SMALL + 256;
constexpr int SM_BAR = SM_O + 128;
constexpr int SM_TOTAL = SM_BAR + 40 * 8;
static_assert(SM_TOTAL <= 232448, "smem");

enum { IT_M = 0, IT_WQ = 1, IT_K = 4, IT_V = 12, IT_WO = 20, IT_W2 = 22, IT_W1 = 24, IT_W2C = 27, IT_W1X = 28,
       BF_WQ = 29, BF_K = 30, BF_X = 31, BF_V0 = 32  , NBAR_USED = 35, NPOS = 28, IT_NONE = 63 };

enum { BX_X2 = 0,
       BX_O = 1024,
       BX_PART = BX_O + NATT * 512,
       BX_MOD = BX_PART + NRED * 512,
       BX_Q = BX_MOD + 864,
       BX_ML = BX_Q + NATT * 8,
       BX_SIDE = BX_ML + NATT * 2,
       BX_EPOCH = BX_SIDE + 32,
       BX_TOTAL = BX_EPOCH + 8 };
static_assert(BX_TOTAL * 16 <= (2 << 20), "mailboxes stay inside one 2 MB page");
__device__ uint4 g_box[(4 << 20) / 16];
__device__ __forceinline__ uint32_t half_of(uint32_t pair, uint32_t side) {
    constexpr uint32_t MASK = ((1u << 13) | (1u << 16) | (1u << 17) | (1u << 19)) >> 4;
    return pair + (((__popc(pair & MASK) ^ side) & 1u) << 8);
}

constexpr unsigned SPIN_MAX = 1u << 21;
#define PIN(x) asm volatile("" : "+r"(x))

__device__ __forceinline__ uint32_t smem_u32(const void* p) { return (uint32_t)__cvta_generic_to_shared(p); }
__device__ __forceinline__ void mbar_init(uint32_t bar, uint32_t cnt) {
    asm volatile("mbarrier.init.shared::cta.b64 [%0], %1;" ::"r"(bar), "r"(cnt) : "memory");
}
__device__ __forceinline__ void mbar_expect_tx(uint32_t bar, uint32_t bytes) {
    asm volatile("mbarrier.arrive.expect_tx.shared::cta.b64 _, [%0], %1;" ::"r"(bar), "r"(bytes) : "memory");
}
__device__ __forceinline__ void mbar_arrive(uint32_t bar) {
    asm volatile("mbarrier.arrive.shared::cta.b64 _, [%0];" ::"r"(bar) : "memory");
}
__device__ __forceinline__ void mbar_wait(uint32_t bar) {
    uint32_t ok;
    unsigned n = 0;
#pragma unroll 1
    do {
        asm volatile("{\n.reg .pred p;\nmbarrier.try_wait.parity.shared::cta.b64 p, [%1], 0;\nselp.u32 %0, 1, 0, p;\n}"
                     : "=r"(ok) : "r"(bar) : "memory");
    } while (!ok && ++n < SPIN_MAX);
}
__device__ __forceinline__ bool mbar_test(uint32_t bar) {
    uint32_t ok;
    asm volatile("{\n.reg .pred p;\nmbarrier.test_wait.parity.shared::cta.b64 p, [%1], 0;\nselp.u32 %0, 1, 0, p;\n}"
                 : "=r"(ok) : "r"(bar) : "memory");
    return __all_sync(0xffffffffu, ok);
}
__device__ __forceinline__ void tma2d(uint32_t dst, const CUtensorMap* map, int c0, int c1, uint32_t bar, uint64_t pol) {
    asm volatile("cp.async.bulk.tensor.2d.shared::cluster.global.mbarrier::complete_tx::bytes.L2::cache_hint [%0], [%1, {%3, %4}], [%2], %5;"
                 ::"r"(dst), "l"(map), "r"(bar), "r"(c0), "r"(c1), "l"(pol) : "memory");
}
__device__ __forceinline__ void cp16(uint32_t dst, const void* src, bool on) {
    asm volatile("{\n.reg .pred p;\nsetp.ne.u32 p, %2, 0;\n@p cp.async.cg.shared.global.L2::128B [%0], [%1], 16;\n}" ::"r"(dst), "l"(src), "r"((uint32_t)on) : "memory");
}
__device__ __forceinline__ void cp_arrive(uint32_t bar) {
    asm volatile("cp.async.mbarrier.arrive.noinc.shared::cta.b64 [%0];" ::"r"(bar) : "memory");
}
__device__ __forceinline__ void cbar() { asm volatile("bar.sync 1, %0;" ::"n"(NCT) : "memory"); }

__device__ __forceinline__ uint32_t lds32(uint32_t a) { uint32_t v; asm volatile("ld.shared.u32 %0, [%1];" : "=r"(v) : "r"(a) : "memory"); return v; }
__device__ __forceinline__ uint32_t lds16(uint32_t a) { uint32_t v; asm volatile("ld.shared.u16 %0, [%1];" : "=r"(v) : "r"(a) : "memory"); return v; }
__device__ __forceinline__ float ldsf(uint32_t a) { float v; asm volatile("ld.shared.f32 %0, [%1];" : "=f"(v) : "r"(a) : "memory"); return v; }
__device__ __forceinline__ float4 ldsf4(uint32_t a) {
    float4 v;
    asm volatile("ld.shared.v4.f32 {%0,%1,%2,%3}, [%4];" : "=f"(v.x), "=f"(v.y), "=f"(v.z), "=f"(v.w) : "r"(a) : "memory");
    return v;
}
__device__ __forceinline__ void sts32(uint32_t a, uint32_t v) { asm volatile("st.shared.u32 [%0], %1;" ::"r"(a), "r"(v) : "memory"); }
__device__ __forceinline__ void sts16(uint32_t a, uint32_t v) { asm volatile("st.shared.u16 [%0], %1;" ::"r"(a), "r"(v) : "memory"); }
__device__ __forceinline__ void stsf(uint32_t a, float v) { asm volatile("st.shared.f32 [%0], %1;" ::"r"(a), "f"(v) : "memory"); }
__device__ __forceinline__ void sts64(uint32_t a, uint32_t x, uint32_t y) { asm volatile("st.shared.v2.u32 [%0], {%1,%2};" ::"r"(a), "r"(x), "r"(y) : "memory"); }

__device__ __forceinline__ void st_msg(uint4* p, uint32_t a, uint32_t b, uint32_t c, uint32_t d) {
    asm volatile("{\n.reg .b128 t;\n.reg .b64 lo, hi;\nmov.b64 lo, {%1, %2};\nmov.b64 hi, {%3, %4};\nmov.b128 t, {lo, hi};\n"
                 "st.relaxed.gpu.global.b128 [%0], t;\n}" ::"l"(p), "r"(a), "r"(b), "r"(c), "r"(d) : "memory");
}
__device__ __forceinline__ uint4 ld_msg(const uint4* p) {
    uint4 v;
    asm volatile("{\n.reg .b128 t;\n.reg .b64 lo, hi;\nld.relaxed.gpu.global.b128 t, [%4];\nmov.b128 {lo, hi}, t;\n"
                 "mov.b64 {%0, %1}, lo;\nmov.b64 {%2, %3}, hi;\n}" : "=r"(v.x), "=r"(v.y), "=r"(v.z), "=r"(v.w) : "l"(p) : "memory");
    return v;
}
template <int BACKOFF = 0>
__device__ __forceinline__ uint4 poll_msg(const uint4* p, uint32_t tag) {
    uint4 v;
    v.w = tag + 1;
    unsigned n = 0;
#pragma unroll 1
    do {
        if (BACKOFF && n) __nanosleep(BACKOFF);
        if (v.w != tag) v = ld_msg(p);
    } while (__any_sync(0xffffffffu, v.w != tag) && ++n < SPIN_MAX);
    return v;
}
__device__ __forceinline__ void st_msg8(uint2* p, uint32_t a, uint32_t b) {
    asm volatile("{\n.reg .b64 t;\nmov.b64 t, {%1, %2};\nst.relaxed.gpu.global.b64 [%0], t;\n}" ::"l"(p), "r"(a), "r"(b) : "memory");
}
__device__ __forceinline__ uint2 ld_msg8(const uint2* p) {
    uint2 v;
    asm volatile("{\n.reg .b64 t;\nld.relaxed.gpu.global.b64 t, [%2];\nmov.b64 {%0, %1}, t;\n}" : "=r"(v.x), "=r"(v.y) : "l"(p) : "memory");
    return v;
}
__device__ __forceinline__ uint32_t ldg16(const __nv_bfloat16* p) {
    uint32_t v;
    asm volatile("ld.global.nc.u16 %0, [%1];" : "=r"(v) : "l"(p));
    return v;
}

__device__ __forceinline__ void ldsm4(uint32_t a, uint32_t* r) {
    asm volatile("ldmatrix.sync.aligned.m8n8.x4.shared.b16 {%0,%1,%2,%3}, [%4];" : "=r"(r[0]), "=r"(r[1]), "=r"(r[2]), "=r"(r[3]) : "r"(a) : "memory");
}
__device__ __forceinline__ void ldsm4t(uint32_t a, uint32_t* r) {
    asm volatile("ldmatrix.sync.aligned.m8n8.x4.trans.shared.b16 {%0,%1,%2,%3}, [%4];" : "=r"(r[0]), "=r"(r[1]), "=r"(r[2]), "=r"(r[3]) : "r"(a) : "memory");
}
__device__ __forceinline__ void ldsm2t(uint32_t a, uint32_t* r) {
    asm volatile("ldmatrix.sync.aligned.m8n8.x2.trans.shared.b16 {%0,%1}, [%2];" : "=r"(r[0]), "=r"(r[1]) : "r"(a) : "memory");
}
__device__ __forceinline__ void mma16(float* c, uint32_t a0, uint32_t a1, uint32_t a2, uint32_t a3, uint32_t b0, uint32_t b1) {
    asm volatile("mma.sync.aligned.m16n8k16.row.col.f32.bf16.bf16.f32 {%0,%1,%2,%3}, {%4,%5,%6,%7}, {%8,%9}, {%0,%1,%2,%3};"
                 : "+f"(c[0]), "+f"(c[1]), "+f"(c[2]), "+f"(c[3]) : "r"(a0), "r"(a1), "r"(a2), "r"(a3), "r"(b0), "r"(b1));
}

__device__ __forceinline__ uint32_t pack2(float lo, float hi) {
    uint32_t r;
    asm("cvt.rn.bf16x2.f32 %0, %1, %2;" : "=r"(r) : "f"(hi), "f"(lo));
    return r;
}
__device__ __forceinline__ float rb(float x) { return __uint_as_float(pack2(0.f, x)); }
__device__ __forceinline__ uint32_t f2b(float x) { return pack2(x, 0.f); }
__device__ __forceinline__ float blo(uint32_t u) { return __uint_as_float(u << 16); }
__device__ __forceinline__ float bhi(uint32_t u) { return __uint_as_float(u & 0xffff0000u); }
__device__ __forceinline__ float ex2(float x) { float r; asm("ex2.approx.ftz.f32 %0, %1;" : "=f"(r) : "f"(x)); return r; }
__device__ __forceinline__ float rcp(float x) { float r; asm("rcp.approx.ftz.f32 %0, %1;" : "=f"(r) : "f"(x)); return r; }
constexpr float LOG2E = 1.4426950408889634f;
__device__ __forceinline__ float sigm(float x) { return rcp(1.f + ex2(-LOG2E * x)); }

__device__ __forceinline__ float3 layernorm3(float3 v, uint32_t scr, uint32_t scr_w, int lane) {
    float s = v.x + v.y + v.z, q = v.x * v.x + v.y * v.y + v.z * v.z;
#pragma unroll
    for (int o = 16; o > 0; o >>= 1) {
        s += __shfl_xor_sync(0xffffffffu, s, o);
        q += __shfl_xor_sync(0xffffffffu, q, o);
    }
    if (lane == 0) sts64(scr_w, __float_as_uint(s), __float_as_uint(q));
    asm volatile("bar.sync 4, 192;" ::: "memory");
    const float4 e0 = ldsf4(scr), e1 = ldsf4(scr + 16), e2 = ldsf4(scr + 32);
    const float mean = ((e0.x + e0.z) + (e1.x + e1.z) + (e2.x + e2.z)) * (1.0f / D);
    const float var = ((e0.y + e0.w) + (e1.y + e1.w) + (e2.y + e2.w)) * (1.0f / D) - mean * mean;
    const float mb = rb(mean);
    float den;
    asm("sqrt.approx.ftz.f32 %0, %1;" : "=f"(den) : "f"(rb(rb(fmaxf(var, 0.f)) + 1e-5f)));
    const float inv = rcp(rb(den));
    return make_float3(rb(rb(v.x - mb) * inv), rb(rb(v.y - mb) * inv), rb(rb(v.z - mb) * inv));
}

template <int NT>
__device__ __forceinline__ void strip_load(uint32_t p4, uint32_t p2, int x, uint32_t (&b)[NT][6]) {
#pragma unroll
    for (int n = 0; n < NT; n++) {
        ldsm4t(p4 + ((n ^ x) << 4), &b[n][0]);
        ldsm2t(p2 + ((n ^ x) << 4), &b[n][4]);
    }
}
__device__ __forceinline__ float red_sum(uint32_t red_r) {
    cbar();
    float v[NCW];
#pragma unroll
    for (int w = 0; w < NCW; w++) v[w] = ldsf(red_r + w * 160);
    return ((v[0] + v[1]) + (v[2] + v[3])) + ((v[4] + v[5]) + (v[6] + v[7])) + ((v[8] + v[9]) + (v[10] + v[11]));
}
template <int NT>
__device__ __forceinline__ void strip_mma_store(const uint32_t (&a)[6], const uint32_t (&b)[NT][6], uint32_t red_w, int lane) {
    float c[NT][4];
#pragma unroll
    for (int n = 0; n < NT; n++) c[n][0] = c[n][1] = c[n][2] = c[n][3] = 0.f;
#pragma unroll
    for (int k = 0; k < 3; k++)
#pragma unroll
        for (int n = 0; n < NT; n++) mma16(c[n], a[2 * k], a[2 * k], a[2 * k + 1], a[2 * k + 1], b[n][2 * k], b[n][2 * k + 1]);
    if (lane < 4) {
#pragma unroll
        for (int n = 0; n < NT; n++) sts64(red_w + n * 32, __float_as_uint(c[n][0]), __float_as_uint(c[n][1]));
    }
}
template <int NT>
__device__ __forceinline__ float strip_mma(const uint32_t (&a)[6], const uint32_t (&b)[NT][6], uint32_t red_w, uint32_t red_r, int lane) {
    strip_mma_store<NT>(a, b, red_w, lane);
    return red_sum(red_r);
}

template <int N>
__device__ __forceinline__ void poll_slots(const uint4* p, uint32_t tag, uint4 (&v)[N]) {
    uint32_t pend = (1u << N) - 1;
    unsigned n = 0;
    bool more;
#pragma unroll 1
    do {
#pragma unroll
        for (int i = 0; i < N; i++) if (pend & (1u << i)) v[i] = ld_msg(p + i * 32);
        uint32_t x = 0;
#pragma unroll
        for (int i = 0; i < N; i++) x |= v[i].w ^ tag;
        more = __any_sync(0xffffffffu, x != 0);
        if (!more) break;
        pend = 0;
#pragma unroll
        for (int i = 0; i < N; i++) pend |= v[i].w != tag ? 1u << i : 0u;
    } while (++n < SPIN_MAX);
}
__device__ __forceinline__ float reduce_part(const uint4* p, uint32_t tag, int lane) {
    uint4 v[8];
    poll_slots<8>(p, tag, v);
#define F(i, c) __uint_as_float(v[i].c)
    float s0 = ((F(0, x) + F(1, x)) + (F(2, x) + F(3, x))) + ((F(4, x) + F(5, x)) + (F(6, x) + F(7, x)));
    float s1 = ((F(0, y) + F(1, y)) + (F(2, y) + F(3, y))) + ((F(4, y) + F(5, y)) + (F(6, y) + F(7, y)));
    float s2 = ((F(0, z) + F(1, z)) + (F(2, z) + F(3, z))) + ((F(4, z) + F(5, z)) + (F(6, z) + F(7, z)));
#undef F
#pragma unroll
    for (int o = 16; o > 1; o >>= 1) {
        s0 += __shfl_xor_sync(0xffffffffu, s0, o);
        s1 += __shfl_xor_sync(0xffffffffu, s1, o);
        s2 += __shfl_xor_sync(0xffffffffu, s2, o);
    }
    return lane < 2 ? s0 : lane < 4 ? s1 : s2;
}

struct Params {
    uint32_t sched[NPOS];
    uint32_t stagger;
    uint32_t probe_deadline;
    const __nv_bfloat16* b2;
    CUtensorMap m_wq, m_k, m_v, m_wo, m_w1, m_w2, m_w1x;
};

__global__ void __launch_bounds__(NTHREADS, 1)
fused_kernel(const __nv_bfloat16* __restrict__ p_wmod, const __nv_bfloat16* __restrict__ p_c, const __nv_bfloat16* __restrict__ p_x,
             uint4* const box, const __nv_bfloat16* __restrict__ p_b1, __nv_bfloat16* __restrict__ p_out,
             const __grid_constant__ Params P) {
    extern __shared__ __align__(1024) unsigned char smem[];
    uint32_t t_start;
    asm volatile("mov.u32 %0, %globaltimer_lo;" : "=r"(t_start));
    uint32_t tid = threadIdx.x, warp = tid >> 5, lane = tid & 31;
    uint32_t cta = blockIdx.x;
    const uint32_t sb = smem_u32(smem);
#define BAR(i) (sb + SM_BAR + (i) * 8)
    {
        const uint32_t row = warp * 48 + (lane >> 2);
        const char* src = reinterpret_cast<const char*>(p_wmod) + (row * (6 * D * 2) + cta * 64 + (lane & 3) * 16);
        const uint32_t d = sb + SM_M + row * 64 + (((lane & 3) ^ ((lane >> 3) & 3)) << 4);
#pragma unroll
        for (int k = 0; k < 6; k++) cp16(d + k * 512, src + k * 8 * (6 * D * 2), warp < NCW && cta < NMOD);
    }
    uint32_t grp = cta >> 3, rk = cta & 7;

    if (warp == NCW) {
        const uint32_t sc = P.sched[min(lane, NPOS - 1u)], stagger = P.stagger;
        const int i = sc & 63;
        int mapi = 1, c0 = 0, c1, bytes = 16384, fbar = -1;
        uint32_t dst;
        if (i < IT_K) {
            mapi = 0; c0 = cta * 32; c1 = (i - IT_WQ) * 192; dst = SM_WQ + (i - IT_WQ) * 12288; bytes = 12288;
        } else if (i < IT_WO) {
            const int k = (i - IT_K) & 7;
            c1 = (grp * SK + (SK - WIN) + ((k >> 1) * 16 + rk * 2 + (k & 1)) * 64) * 2;
            dst = SM_K + k * 16384;
            if (i >= IT_V) {
                mapi = 2; dst = SM_RING + (k < 5 ? k : k - 5) * 16384;
                fbar = k == 0 ? BF_WQ : k >= 5 ? BF_V0 + k - 5 : -1;
            }
        } else if (i < IT_W2) {
            mapi = 3; c1 = (grp * 256 + (i - IT_WO) * 128 + rk * 16) * 9; dst = SM_WO + (i - IT_WO) * 18432; bytes = 18432;
            fbar = BF_K;
        } else if (i < IT_W1) {
            mapi = 5; c1 = (cta * 32 + (i - IT_W2) * 16) * 9; dst = SM_W2 + (i - IT_W2) * 18432; bytes = 18432;
        } else if (i < IT_W2C) {
            mapi = 4; c0 = cta * 32; c1 = (i - IT_W1) * 192; dst = SM_W1 + (i - IT_W1) * 12288; bytes = 12288;
        } else if (i == IT_W2C) {
            mapi = 5; c1 = (4096 + (cta - NRED) * 16) * 9; dst = SM_W2 + 2 * 18432; bytes = cta >= NRED ? 18432 : 0;
        } else {
            mapi = 6; c0 = 4096 + (cta - NRED) * 16; c1 = 0; dst = SM_W1X; bytes = cta >= NRED ? 18432 : 0;
            fbar = BF_X;
        }
        uint64_t pol;
        asm volatile("createpolicy.fractional.L2::evict_first.b64 %0, 1.0;" : "=l"(pol));
        const uint32_t t_iss = t_start + (sc >> 16) + ((((sc >> 12) & 15) * ((cta + 32) & 127) * stagger) >> 10);
        const CUtensorMap* map = &P.m_wq + mapi;
        const uint32_t gates = ((sc >> 6) & 63) | ((uint32_t)(fbar & 63) << 8);
        asm volatile("bar.sync 2, %0;" ::"n"(NTHREADS) : "memory");
#pragma unroll 1
        for (int k = cta >= NMOD ? 3 : 0; k < NPOS; k++) {
            const uint32_t gk = __shfl_sync(0xffffffffu, gates, k);
            const uint32_t tk = __shfl_sync(0xffffffffu, t_iss, k);
            if ((gk & 63) != IT_NONE) mbar_wait(BAR(gk & 63));
            if ((gk >> 8) != IT_NONE) mbar_wait(BAR(gk >> 8));
            uint32_t now;
            unsigned n = 0;
            do { asm volatile("mov.u32 %0, %globaltimer_lo;" : "=r"(now)); } while ((int)(now - tk) < 0 && ++n < SPIN_MAX);
            if (lane == k && bytes) {
                const uint32_t bk = BAR(i);
                mbar_expect_tx(bk, bytes);
                tma2d(sb + dst, map, c0, c1, bk, pol);
                if (mapi == 6) { tma2d(sb + dst + 6144, map, c0, 192, bk, pol); tma2d(sb + dst + 12288, map, c0, 384, bk, pol); }
            }
            __syncwarp();
        }
        return;
    }

    if (warp > NCW) {
        if (lane == 0) {
#pragma unroll
            for (int i = 0; i < NBAR_USED; i++) mbar_init(BAR(i), i == IT_M ? NCT : i >= BF_X ? 4 : 1);
            asm volatile("fence.mbarrier_init.release.cluster;" ::: "memory");
        }
        __syncwarp();
        asm volatile("bar.arrive 2, %0;" ::"n"(NTHREADS) : "memory");
        if (lane == 0 && cta >= NMOD) {
            uint64_t pol;
            asm volatile("createpolicy.fractional.L2::evict_first.b64 %0, 1.0;" : "=l"(pol));
#pragma unroll
            for (int i = 0; i < 3; i++) {
                mbar_expect_tx(BAR(IT_WQ + i), 12288);
                tma2d(sb + SM_WQ + i * 12288, &P.m_wq, cta * 32, i * 192, BAR(IT_WQ + i), pol);
            }
        }
        __syncwarp();
        st_msg(box + half_of(BX_O + cta * 512, (lane >> 1) & 1) + 128 + (lane >> 2) * 16 + (lane & 1), 0u, 0u, 0u, 0u);
        uint32_t epoch;
        asm volatile("ld.relaxed.gpu.global.u32 %0, [%1];" : "=r"(epoch) : "l"(box + BX_EPOCH) : "memory");
        if (lane < 7) asm volatile("prefetch.tensormap [%0];" ::"l"(&P.m_wq + lane) : "memory");
        lane = __shfl_sync(0xffffffffu, lane, lane); cta = __shfl_sync(0xffffffffu, cta, 0);
        if (lane == 0) {
            uint32_t best0 = 0xffffffffu, best1 = 0xffffffffu, prev = 0;
            int wins = 0;
            bool clear = false;
#pragma unroll 1
            for (uint32_t r = 0; r < 80; r++) {
                uint32_t c0, c1 = 0;
                asm volatile("{\n.reg .pred p;\n.reg .u32 v;\nmov.u32 %0, %clock;\natom.relaxed.gpu.global.exch.b32 v, [%2], 0;\n"
                             "setp.ne.u32 p, v, 1;\n@p mov.u32 %1, %clock;\n}" : "=r"(c0), "+r"(c1)
                             : "l"(box + half_of(BX_O + cta * 512, r & 1) + 128 + ((r >> 1) & 7) * 16) : "memory");
                const uint32_t d = c1 - c0;
                if (r & 1) best1 = min(best1, d); else best0 = min(best0, d);
                if (r >= 3) wins += ((d < prev) == (r & 1)) ? 1 : -1;
                prev = d;
                const uint32_t lo = min(best0, best1), hi = max(best0, best1);
                clear = lo < 380 && lo * 10 < hi * 8;
                uint32_t now;
                asm volatile("mov.u32 %0, %globaltimer_lo;" : "=r"(now));
                if (r >= 3 && (clear || now - t_start > P.probe_deadline)) break;
            }
            uint32_t smid;
            asm volatile("mov.u32 %0, %smid;" : "=r"(smid));
            const uint32_t side = (clear || wins == 0) ? best1 < best0 : wins > 0;
            asm volatile("st.relaxed.gpu.global.u32 [%0], %1;" ::"l"(reinterpret_cast<uint32_t*>(box + BX_SIDE) + cta),
                         "r"(((epoch * 2 + 1) << 16) | ((smid >> 1) << 2) | (clear ? 2u : 0u) | side) : "memory");
        }
        __syncwarp();
        const uint32_t tag = epoch * 2 + 1;
        const uint32_t rcol = min(48 * (cta >> 3) + 8 * min(lane, 5u) + (cta & 7), D - 1u);
        const uint32_t rx = ldg16(p_x + rcol), rb2 = ldg16(P.b2 + rcol);
        const uint32_t rb1 = ldg16(p_b1 + cta * 32 + lane), rb1x = ldg16(p_b1 + 4096 + (cta & 31) * 16 + (lane & 15));
        __nv_bfloat16* const op = p_out + rcol;
        uint2* const x2_dst = reinterpret_cast<uint2*>(box + half_of(BX_X2 + ((lane >> 3) & 1) * 512, lane >> 1) + ((lane >> 2) & 1) * 128) +
                              (cta * 2 + (lane & 1));
        if (cta < NRED && lane < 16) st_msg8(x2_dst, 0u, 0u);
        mbar_wait(BAR(IT_K + 4));
        float ga, gb;
        {
            const uint4 va = poll_msg<200>(box + BX_MOD + (2 * D + rcol) / 4, tag), vb = poll_msg<200>(box + BX_MOD + (5 * D + rcol) / 4, tag);
            const uint32_t ua = rcol & 2 ? va.y : va.x, ub = rcol & 2 ? vb.y : vb.x;
            ga = rcol & 1 ? bhi(ua) : blo(ua);
            gb = rcol & 1 ? bhi(ub) : blo(ub);
        }
        asm volatile("bar.sync 3, %0;" ::"n"(NCT + 32) : "memory");
        const uint32_t side = lds32(sb + SM_XN + cta * 4);
        const uint4* part_src = box + (half_of(BX_PART + min(cta, NRED - 1u) * 512, side) + lane);
        {
            const uint4* src = box + (half_of(BX_O + cta * 512, side) + lane);
            mbar_wait(BAR(IT_V + 7));
            uint4 v[4];
            poll_slots<4>(src, tag, v);
            float o0 = (__uint_as_float(v[0].x) + __uint_as_float(v[1].x)) + (__uint_as_float(v[2].x) + __uint_as_float(v[3].x));
            float o1 = (__uint_as_float(v[0].y) + __uint_as_float(v[1].y)) + (__uint_as_float(v[2].y) + __uint_as_float(v[3].y));
            const float o = (lane < 16 ? o0 : o1) + __shfl_xor_sync(0xffffffffu, lane < 16 ? o1 : o0, 16);
            sts16(sb + SM_O + lane * 2, f2b(o));
            asm volatile("bar.arrive 10, %0;" ::"n"(NCT + 32) : "memory");
        }
        float r_x2 = 0.f;
        if (cta < NRED) {
            mbar_wait(BAR(IT_WO + 1));
            const float sv = reduce_part(part_src, tag, lane);
            r_x2 = rb(blo(rx) + rb(ga * rb(sv)));
            const uint32_t w = __float_as_uint(r_x2);
            const uint32_t w0 = __shfl_sync(0xffffffffu, w, lane & 1), w1 = __shfl_sync(0xffffffffu, w, (lane & 1) + 2),
                           w2 = __shfl_sync(0xffffffffu, w, (lane & 1) + 4);
            if (lane < 16) st_msg8(x2_dst, (w0 >> 16) | w1, (w2 >> 16) | (tag << 16));
            __syncwarp();
            asm volatile("bar.arrive 9, 224;" ::: "memory");
        }
        {
            asm volatile("bar.sync 8, %0;" ::"n"(NCT + 32) : "memory");
            uint32_t hv[2];
#pragma unroll
            for (int k = 0; k < 2; k++) {
                const uint32_t ra = sb + SM_RED + (k ? 32 + (lane & 15) : lane) * 48;
                const float4 p0 = ldsf4(ra), p1 = ldsf4(ra + 16), p2 = ldsf4(ra + 32);
                const float r = ((p0.x + p0.y) + (p0.z + p0.w)) + ((p1.x + p1.y) + (p1.z + p1.w)) + ((p2.x + p2.y) + (p2.z + p2.w));
                const float u = rb(rb(r) + blo(k ? rb1x : rb1));
                const float z = 1.5957691216057308f * (u + 0.044715f * u * u * u);
                hv[k] = f2b(u * sigm(z));
            }
            sts16(sb + SM_O + lane * 2, hv[0]);
            if (lane < 16) sts16(sb + SM_O + 64 + lane * 2, hv[1]);
            __syncwarp();
            asm volatile("bar.arrive 6, %0;" ::"n"(NCT + 32) : "memory");
        }
        if (cta < NRED) {
            mbar_wait(BAR(IT_W2 + 1));
            const float sv = reduce_part(part_src, tag + 1, lane);
            const uint32_t y = f2b(r_x2 + rb(gb * rb(rb(sv) + blo(rb2))));
            if (lane < 6) asm volatile("st.global.u16 [%0], %1;" ::"l"(op), "r"(y) : "memory");
            if (cta == 0 && lane == 0) asm volatile("st.relaxed.gpu.global.u32 [%0], %1;" ::"l"(box + BX_EPOCH), "r"(epoch + 1) : "memory");
        }
        return;
    }

    tid = __shfl_sync(0xffffffffu, tid, lane); cta = __shfl_sync(0xffffffffu, cta, 0);
    warp = tid >> 5; lane = tid & 31; grp = cta >> 3; rk = cta & 7;
    const uint32_t t = lane & 3, gq = lane >> 2;
    const uint32_t li = tid - 64;
    const bool is_ln = li < 192;
    const uint32_t lcol = is_ln ? 48 * (li >> 4) + 8 * (li & 1) + ((li >> 1) & 7) : 0;
    const uint32_t vi = warp * 24 + min(lane, 23u);
    uint32_t cv = 0, epoch = 0, x0 = 0, x1 = 0, x2 = 0;
    if (cta < NMOD) asm volatile("ld.global.nc.u32 %0, [%1];" : "=r"(cv) : "l"(reinterpret_cast<const uint32_t*>(p_c) + vi));
    if (warp == 0) asm volatile("ld.relaxed.gpu.global.u32 %0, [%1];" : "=r"(epoch) : "l"(box + BX_EPOCH) : "memory");
    if (is_ln) { x0 = ldg16(p_x + li); x1 = ldg16(p_x + li + 192); x2 = ldg16(p_x + li + 384); }
    asm volatile("cp.async.commit_group;" ::: "memory");
    asm volatile("bar.sync 2, %0;" ::"n"(NTHREADS) : "memory");
    cp_arrive(BAR(IT_M));
    if (warp == 8) {
        const uint32_t idx = lane < 8 ? BX_MOD + cta * 8 + lane : lane < 16 ? BX_Q + cta * 8 + lane - 8 : BX_ML + cta * 2 + lane - 16;
        if (lane < 18 && (lane >= 8 || cta < NMOD)) st_msg(box + idx, 0u, 0u, 0u, 0u);
    }
    uint32_t a[6];
    {
        PIN(cv);
        const float c0 = blo(cv), c1 = bhi(cv);
        const uint32_t av = pack2(c0 * sigm(c0), c1 * sigm(c1));
#pragma unroll
        for (int i = 0; i < 6; i++) a[i] = __shfl_sync(0xffffffffu, av, i * 4 + t);
    }
    const uint32_t scr_w = sb + SM_SMALL + (warp - 2) * 8;
    PIN(x0); PIN(x1); PIN(x2);
    if (is_ln) {
        const float3 xv = layernorm3(make_float3(blo(x0), blo(x1), blo(x2)), sb + SM_SMALL + 192, scr_w + 192, lane);
        sts16(sb + SM_XN + li * 2, __float_as_uint(xv.x) >> 16);
        sts16(sb + SM_XN + li * 2 + 384, __float_as_uint(xv.y) >> 16);
        sts16(sb + SM_XN + li * 2 + 768, __float_as_uint(xv.z) >> 16);
    }
    uint32_t tag = epoch * 2 + 1;
    if (tid == 0) sts32(sb + SM_O + 124, tag);
    const uint32_t red_w = sb + SM_RED + warp * 160 + lane * 8, red_r = sb + SM_RED + min(tid, 39u) * 4;
    const uint32_t r4 = warp * 48 + lane, r2 = warp * 48 + 32 + (lane & 15);

    asm volatile("cp.async.wait_group 0;" ::: "memory");
    asm volatile("fence.proxy.async.shared::cta;" ::: "memory");
    __syncwarp();
    const bool extra = cta >= NRED;
    const uint32_t w1row = warp * 48 + (lane & 7) + 8 * (lane >> 4);
#pragma unroll 1
    for (uint32_t ph = cta < NMOD ? 0 : 1; ph < 2; ph++) {
        if (ph) {
            cbar();
            tag = lds32(sb + SM_O + 124);
            const uint32_t l24 = min(lane, 23u), sl = (l24 >= 12 ? 132 : 0) + warp * 12 + l24;
            mbar_wait(BAR(IT_WQ + 1));
            const uint4 v = poll_msg<250>(box + BX_MOD + sl, tag);
            sts64(sb + SM_MOD + sl * 8, v.x, v.y);
            __syncwarp();
            const uint32_t xn = lds32(sb + SM_XN + vi * 4), sa = lds32(sb + SM_MOD + vi * 4), ca = lds32(sb + SM_MOD + 1152 + vi * 4);
            const uint32_t one = pack2(1.f + blo(ca), 1.f + bhi(ca));
            const uint32_t pr = pack2(blo(xn) * blo(one), bhi(xn) * bhi(one));
            const uint32_t av = pack2(blo(pr) + blo(sa), bhi(pr) + bhi(sa));
#pragma unroll
            for (int i = 0; i < 6; i++) a[i] = __shfl_sync(0xffffffffu, av, i * 4 + t);
            mbar_wait(BAR(IT_WQ + (warp >> 2)));
        }
        uint32_t b[4][6];
        strip_load<4>(sb + SM_M + ph * 36864 + r4 * 64, sb + SM_M + ph * 36864 + r2 * 64, (lane >> 1) & 3, b);
        const float r = strip_mma<4>(a, b, red_w, red_r, lane);
        if (warp == 0) {
            sts16(sb + SM_O + lane * 2, f2b(r));
            __syncwarp();
            if (lane < 8) st_msg(box + (ph ? BX_Q : BX_MOD) + cta * 8 + lane, lds32(sb + SM_O + lane * 8), lds32(sb + SM_O + lane * 8 + 4), 0u, tag);
        }
    }
    if (tid == 0) mbar_arrive(BAR(BF_WQ));
    if (li < 64) {
        const uint4 v = poll_msg<200>(box + BX_Q + grp * 64 + li, tag);
        sts64(sb + SM_Q + li * 8, v.x, v.y);
    }
    cbar();
    const uint32_t ob = sb + SM_O + t * 4;

    if (warp < 8) {
        uint32_t bq[4][2];
        const uint32_t msk = gq < 4 ? 0xffffffffu : 0u;
#pragma unroll
        for (int ks = 0; ks < 4; ks++) {
            const uint32_t qa = sb + SM_Q + ((gq & 1) * 64 + (gq & 2) * 16 + ks * 8 + t) * 4;
            bq[ks][0] = lds32(qa) & msk;
            bq[ks][1] = lds32(qa + 16) & msk;
        }
        float mx0 = -INFINITY, mx1 = -INFINITY;
        uint32_t rowaddr = sb + SM_K + (warp * 16 + (lane & 15)) * 128;
        const uint32_t xo = (lane >> 4) ^ (lane & 7);
        uint32_t sa = sb + SM_S + (warp * 8 + (lane >> 3)) * 4;
#pragma unroll 1
        for (int ch = 0; ch < 8; ch += 2) {
            uint32_t ka[2][4][4];
#pragma unroll
            for (int u = 0; u < 2; u++) {
                mbar_wait(BAR(IT_K + ch + u));
#pragma unroll
                for (int ks = 0; ks < 4; ks++) ldsm4(rowaddr + u * 16384 + (((2 * ks) ^ xo) << 4), ka[u][ks]);
            }
            float c[2][4];
#pragma unroll
            for (int u = 0; u < 2; u++) c[u][0] = c[u][1] = c[u][2] = c[u][3] = 0.f;
#pragma unroll
            for (int ks = 0; ks < 4; ks++)
#pragma unroll
                for (int u = 0; u < 2; u++)
                    mma16(c[u], ka[u][ks][0], ka[u][ks][1], ka[u][ks][2], ka[u][ks][3], bq[ks][0], bq[ks][1]);
            const float sc = 0.08838834764831845f;
#pragma unroll
            for (int u = 0; u < 2; u++) {
#pragma unroll
                for (int i = 0; i < 4; i++) c[u][i] = rb(rb(c[u][i] + __shfl_down_sync(0xffffffffu, c[u][i], 5)) * sc);
                if ((lane & 7) == 0) {
                    const uint32_t d = sa + u * 256;
                    stsf(d, c[u][0]); stsf(d + 2048, c[u][1]); stsf(d + 16, c[u][2]); stsf(d + 2064, c[u][3]);
                }
                mx0 = fmaxf(mx0, fmaxf(c[u][0], c[u][2]));
                mx1 = fmaxf(mx1, fmaxf(c[u][1], c[u][3]));
            }
            rowaddr += 32768; sa += 512;
        }
#pragma unroll
        for (int o = 8; o <= 16; o <<= 1) {
            mx0 = fmaxf(mx0, __shfl_xor_sync(0xffffffffu, mx0, o));
            mx1 = fmaxf(mx1, __shfl_xor_sync(0xffffffffu, mx1, o));
        }
        if (lane == 0) { stsf(sb + SM_SMALL + warp * 4, mx0); stsf(sb + SM_SMALL + 32 + warp * 4, mx1); }
        asm volatile("bar.sync 5, 256;" ::: "memory");
        if (tid == 0) mbar_arrive(BAR(BF_K));
        const uint32_t hd = warp >> 2;
        const float4 ma = ldsf4(sb + SM_SMALL + hd * 32), mb = ldsf4(sb + SM_SMALL + hd * 32 + 16);
        const float4 s4 = ldsf4(sb + SM_S + tid * 16);
        const float m = fmaxf(fmaxf(fmaxf(ma.x, ma.y), fmaxf(ma.z, ma.w)), fmaxf(fmaxf(mb.x, mb.y), fmaxf(mb.z, mb.w)));
        const float p0 = ex2((s4.x - m) * LOG2E), p1 = ex2((s4.y - m) * LOG2E), p2 = ex2((s4.z - m) * LOG2E), p3 = ex2((s4.w - m) * LOG2E);
        sts64(sb + SM_P + tid * 8, pack2(p0, p1), pack2(p2, p3));
        float l = (p0 + p1) + (p2 + p3);
#pragma unroll
        for (int o = 16; o > 0; o >>= 1) l += __shfl_xor_sync(0xffffffffu, l, o);
        if (lane == 0) { stsf(sb + SM_SMALL + 128 + warp * 4, l); stsf(sb + SM_SMALL + 160 + hd * 4, m); }
        asm volatile("bar.sync 5, 256;" ::: "memory");
    }

    uint32_t wad[3];
#pragma unroll
    for (int i = 0; i < 3; i++) {
        const uint32_t T = warp * 3 + i, blk = T >> 2, ch = 2 * (T & 3) + ((lane >> 3) & 1);
        const uint32_t fr = ((lane & 7) + 8 * (lane >> 4)) * 9 + blk;
        wad[i] = sb + fr * 128 + ((ch ^ (fr & 7)) << 4);
        PIN(wad[i]);
    }
    if (warp < 4) {
        float c[2][4];
#pragma unroll
        for (int i = 0; i < 2; i++) c[i][0] = c[i][1] = c[i][2] = c[i][3] = 0.f;
        const uint32_t row = (lane & 7) + 8 * (lane >> 4);
        const uint32_t off = sb + SM_RING + row * 128 + (((2 * warp + ((lane >> 3) & 1)) ^ (lane & 7)) << 4);
        uint32_t pp = sb + SM_P + ((gq & 1) * 512 + t) * 2;
        const uint32_t mul = gq < 2 ? 1u : gq < 4 ? 65536u : 0u;
        float f0 = 0.f, f1 = 0.f;
        uint4* o_dst = box;
        uint32_t slot = 0;
#pragma unroll 1
        for (int ch = 0; ch < 8; ch++) {
            uint32_t bp[16];
#pragma unroll
            for (int i = 0; i < 16; i++) bp[i] = lds16(pp + i * 8) * mul;
            if (ch == 7) {
                asm volatile("bar.sync 3, %0;" ::"n"(NCT + 32) : "memory");
                f0 = ldsf(sb + SM_SMALL + 176); f1 = ldsf(sb + SM_SMALL + 180);
                const uint32_t ro = grp * 8 + (t & 1) * 4 + warp;
                o_dst = box + (half_of(BX_O + ro * 512, lds32(sb + SM_XN + ro * 4)) + rk * 16 + gq);
            }
            uint32_t base = off + slot * 16384;
            PIN(base);
            mbar_wait(BAR(IT_V + ch));
            uint32_t va[8][4];
#pragma unroll
            for (int ks = 0; ks < 8; ks++) ldsm4t(base + ks * 2048, va[ks]);
#pragma unroll
            for (int ks = 0; ks < 8; ks++) mma16(c[ks & 1], va[ks][0], va[ks][1], va[ks][2], va[ks][3], bp[2 * ks], bp[2 * ks + 1]);
            if ((ch < 3 || ch == 4) && lane == 0) mbar_arrive(BAR(ch == 4 ? BF_X : BF_V0 + ch));
            slot = slot == 4 ? 0 : slot + 1;
            pp += 128;
        }
        if (t < 2) {
            st_msg(o_dst, __float_as_uint((c[0][0] + c[1][0]) * f0), __float_as_uint((c[0][1] + c[1][1]) * f1), 0u, tag);
            st_msg(o_dst + 8, __float_as_uint((c[0][2] + c[1][2]) * f0), __float_as_uint((c[0][3] + c[1][3]) * f1), 0u, tag);
        }
    } else {
        if (warp == 4) {
            const uint32_t hd = lane & 1;
            const float m_own = ldsf(sb + SM_SMALL + 160 + hd * 4);
            const float4 l4 = ldsf4(sb + SM_SMALL + 128 + hd * 16);
            if (lane < 2) st_msg(box + BX_ML + cta * 2 + lane, __float_as_uint(m_own), __float_as_uint((l4.x + l4.y) + (l4.z + l4.w)), 0u, tag);
            mbar_wait(BAR(IT_V + 3));
            const uint4 v = poll_msg<300>(box + BX_ML + grp * 16 + (lane & 15), tag);
            const float ms = __uint_as_float(v.x);
            float M = ms;
#pragma unroll
            for (int o = 2; o <= 8; o <<= 1) M = fmaxf(M, __shfl_xor_sync(0xffffffffu, M, o));
            float L = __uint_as_float(v.y) * ex2((ms - M) * LOG2E);
#pragma unroll
            for (int o = 2; o <= 8; o <<= 1) L += __shfl_xor_sync(0xffffffffu, L, o);
            if (lane < 2) stsf(sb + SM_SMALL + 176 + lane * 4, ex2((m_own - M) * LOG2E) * rcp(L));
        } else if (warp >= 8) {
#pragma unroll 1
            for (uint32_t i = tid - 256; i < 288; i += 128) {
                const uint4 v = poll_msg<200>(box + BX_MOD + 432 + i, tag);
                sts64(sb + SM_MOD + i * 8, v.x, v.y);
            }
            mbar_wait(BAR(IT_V + 2));
            const uint32_t u = tid - 256;
            const uint32_t* side = reinterpret_cast<const uint32_t*>(box + BX_SIDE) + u;
            uint32_t sp;
            unsigned n = 0;
#pragma unroll 1
            do {
                if (n) __nanosleep(500);
                asm volatile("ld.relaxed.gpu.global.u32 %0, [%1];" : "=r"(sp) : "l"(side) : "memory");
            } while (__any_sync(0xffffffffu, (sp >> 16) != (tag & 0xffffu)) && ++n < SPIN_MAX);
            const uint32_t nb = __shfl_xor_sync(0xffffffffu, sp, 1);
            sts32(sb + SM_XN + u * 4, (((sp ^ nb) >> 1) == 1 && (nb & 2) ? nb : sp) & 1);
            asm volatile("bar.sync 7, 128;" ::: "memory");
#pragma unroll
            for (int k = 0; k < 2; k++) {
                const uint32_t rp = k * 64 + (u >> 1);
                if (rp < NRED) st_msg(box + (half_of(BX_PART + rp * 512, lds32(sb + SM_XN + rp * 4)) + cta * 2 + (u & 1)), 0u, 0u, 0u, 0u);
            }
            const uint32_t ro = grp * 8 + (u >> 4);
            st_msg(box + (half_of(BX_O + ro * 512, lds32(sb + SM_XN + ro * 4)) + rk * 16 + (u & 15)), 0u, 0u, 0u, 0u);
            asm volatile("bar.arrive 3, %0;" ::"n"(NCT + 32) : "memory");
        }
        if (warp < 8) asm volatile("bar.sync 3, %0;" ::"n"(NCT + 32) : "memory");
    }

    uint4* const part_dst = box + (half_of(BX_PART + (warp * 8 + gq) * 512, lds32(sb + SM_XN + (warp * 8 + gq) * 4)) + cta * 2 + (t & 1));
    const uint32_t my_side = lds32(sb + SM_XN + cta * 4);
    {
        uint32_t wa[3][8];
        mbar_wait(BAR(IT_WO));
#pragma unroll
        for (int i = 0; i < 3; i++) ldsm4t(wad[i] + SM_WO, &wa[i][0]);
        const bool pre0 = mbar_test(BAR(IT_WO + 1));
        if (pre0) {
#pragma unroll
            for (int i = 0; i < 3; i++) ldsm4t(wad[i] + SM_WO + 16 * 1152, &wa[i][4]);
        }
        asm volatile("bar.sync 10, %0;" ::"n"(NCT + 32) : "memory");
        const uint32_t b0 = lds32(ob), b1 = lds32(ob + 16), b2 = lds32(ob + 32), b3 = lds32(ob + 48);
        float c[3][4];
#pragma unroll
        for (int i = 0; i < 3; i++) {
            c[i][0] = c[i][1] = c[i][2] = c[i][3] = 0.f;
            mma16(c[i], wa[i][0], wa[i][1], wa[i][2], wa[i][3], b0, b1);
        }
        if (!pre0) {
            mbar_wait(BAR(IT_WO + 1));
#pragma unroll
            for (int i = 0; i < 3; i++) ldsm4t(wad[i] + SM_WO + 16 * 1152, &wa[i][4]);
        }
#pragma unroll
        for (int i = 0; i < 3; i++) mma16(c[i], wa[i][4], wa[i][5], wa[i][6], wa[i][7], b2, b3);
        if (t < 2) st_msg(part_dst, __float_as_uint(t ? c[0][2] : c[0][0]), __float_as_uint(t ? c[1][2] : c[1][0]),
                          __float_as_uint(t ? c[2][2] : c[2][0]), tag);
    }
    uint32_t wb[6][4], wx[3][4];
    const uint32_t w1bar = BAR((lane & 1) && extra ? IT_W1X : IT_W1 + (warp >> 2));
    const uint32_t w1a = sb + SM_W1 + w1row * 64 + ((((lane >> 3) & 1) ^ ((lane >> 1) & 3)) << 4);
    const uint32_t w1x = sb + SM_W1X + w1row * 32 + ((lane >> 3) & 1) * 16;
#define W1_LOAD() do { _Pragma("unroll") for (int k = 0; k < 3; k++) { \
        if (extra) ldsm4t(w1x + k * 512, wx[k]); \
        ldsm4t(w1a + k * 1024, wb[k * 2]); ldsm4t((w1a ^ 32) + k * 1024, wb[k * 2 + 1]); } } while (0)
    bool pre1 = false;
    if (is_ln) {
        const uint32_t ma = sb + SM_MOD + lcol * 2;
        float c0 = rb(1.f + blo(lds16(ma + 2 * D))), c1 = rb(1.f + blo(lds16(ma + 2 * D + 32))), c2 = rb(1.f + blo(lds16(ma + 2 * D + 64)));
        float s0 = blo(lds16(ma)), s1 = blo(lds16(ma + 32)), s2 = blo(lds16(ma + 64));
        const uint2* src = reinterpret_cast<const uint2*>(box + half_of(BX_X2 + (cta & 2) * 256, my_side) + (cta & 1) * 128) + li;
        const uint32_t yd = sb + SM_VEC + lcol * 2;
        uint2 v;
        bool xp = true;
        unsigned n = 0;
        if (cta < NRED) asm volatile("bar.sync 9, 224;" ::: "memory");
        else mbar_wait(w1bar);
        pre1 = mbar_test(w1bar);
        if (pre1) W1_LOAD();
#pragma unroll 1
        do { if (xp) v = ld_msg8(src); xp = (v.y >> 16) != (tag & 0xffffu); } while (__any_sync(0xffffffffu, xp) && ++n < SPIN_MAX);
        float3 y = layernorm3(make_float3(blo(v.x), bhi(v.x), blo(v.y)), sb + SM_SMALL, scr_w, lane);
        y = layernorm3(make_float3(rb(rb(y.x * c0) + s0), rb(rb(y.y * c1) + s1), rb(rb(y.z * c2) + s2)), sb + SM_SMALL + 64, scr_w + 64, lane);
        sts16(yd, __float_as_uint(y.x) >> 16); sts16(yd + 32, __float_as_uint(y.y) >> 16); sts16(yd + 64, __float_as_uint(y.z) >> 16);
    }
    {
        const uint32_t ya = sb + SM_VEC + (warp * 24 + t) * 4;
        const uint32_t rd = sb + SM_RED + (t * 16 + gq) * 48 + warp * 4;
        if (!pre1) {
            mbar_wait(w1bar);
            __syncwarp();
            W1_LOAD();
        }
        cbar();
#pragma unroll
        for (int i = 0; i < 6; i++) a[i] = lds32(ya + i * 16);
        float c[3][4];
#pragma unroll
        for (int j = 0; j < 3; j++) c[j][0] = c[j][1] = c[j][2] = c[j][3] = 0.f;
#pragma unroll
        for (int k = 0; k < 3; k++) {
#pragma unroll
            for (int j = 0; j < 2; j++) mma16(c[j], wb[k * 2 + j][0], wb[k * 2 + j][1], wb[k * 2 + j][2], wb[k * 2 + j][3], a[2 * k], a[2 * k + 1]);
            if (extra) mma16(c[2], wx[k][0], wx[k][1], wx[k][2], wx[k][3], a[2 * k], a[2 * k + 1]);
        }
        if (t < 3) {
            stsf(rd, t == 0 ? c[0][0] : t == 1 ? c[1][0] : c[2][0]);
            stsf(rd + 8 * 48, t == 0 ? c[0][2] : t == 1 ? c[1][2] : c[2][2]);
        }
        asm volatile("bar.arrive 8, %0;" ::"n"(NCT + 32) : "memory");
    }
    {
        uint32_t wa[3][12];
        mbar_wait(BAR((lane & 1) && extra ? IT_W2C : IT_W2));
        __syncwarp();
#pragma unroll
        for (int i = 0; i < 3; i++) {
            ldsm4t(wad[i] + SM_W2, &wa[i][0]);
            if (extra) ldsm4t(wad[i] + SM_W2 + 32 * 1152, &wa[i][8]);
        }
        const bool pre = mbar_test(BAR(IT_W2 + 1));
        if (pre) {
#pragma unroll
            for (int i = 0; i < 3; i++) ldsm4t(wad[i] + SM_W2 + 16 * 1152, &wa[i][4]);
        }
        asm volatile("bar.sync 6, %0;" ::"n"(NCT + 32) : "memory");
        uint32_t b[6];
#pragma unroll
        for (int i = 0; i < 6; i++) b[i] = lds32(ob + i * 16);
        float c[3][4], e[3][4], f[3][4];
#pragma unroll
        for (int i = 0; i < 3; i++) {
#pragma unroll
            for (int j = 0; j < 4; j++) c[i][j] = e[i][j] = f[i][j] = 0.f;
            mma16(c[i], wa[i][0], wa[i][1], wa[i][2], wa[i][3], b[0], b[1]);
            if (extra) mma16(e[i], wa[i][8], wa[i][9], wa[i][10], wa[i][11], b[4], b[5]);
        }
        if (!pre) {
            mbar_wait(BAR(IT_W2 + 1));
#pragma unroll
            for (int i = 0; i < 3; i++) ldsm4t(wad[i] + SM_W2 + 16 * 1152, &wa[i][4]);
        }
#pragma unroll
        for (int i = 0; i < 3; i++) mma16(f[i], wa[i][4], wa[i][5], wa[i][6], wa[i][7], b[2], b[3]);
        float r[3];
#pragma unroll
        for (int i = 0; i < 3; i++) r[i] = t ? (c[i][2] + e[i][2]) + f[i][2] : (c[i][0] + e[i][0]) + f[i][0];
        if (t < 2) st_msg(part_dst, __float_as_uint(r[0]), __float_as_uint(r[1]), __float_as_uint(r[2]), tag + 1);
    }
#undef BAR
}

typedef CUresult (*EncodeFn)(CUtensorMap*, CUtensorMapDataType, cuuint32_t, void*, const cuuint64_t*, const cuuint64_t*,
                             const cuuint32_t*, const cuuint32_t*, CUtensorMapInterleave, CUtensorMapSwizzle,
                             CUtensorMapL2promotion, CUtensorMapFloatOOBfill);

void make_map(EncodeFn enc, CUtensorMap* m, const void* base, uint64_t cols, uint64_t rows, uint32_t bc, uint32_t br,
              CUtensorMapSwizzle sw, CUtensorMapL2promotion promo) {
    cuuint64_t dims[2] = {cols, rows};
    cuuint64_t strides[1] = {cols * 2};
    cuuint32_t box[2] = {bc, br};
    cuuint32_t es[2] = {1, 1};
    enc(m, CU_TENSOR_MAP_DATA_TYPE_BFLOAT16, 2, const_cast<void*>(base), dims, strides, box, es,
        CU_TENSOR_MAP_INTERLEAVE_NONE, sw, promo, CU_TENSOR_MAP_FLOAT_OOB_FILL_NONE);
}

struct Tune { int t0, rate, stagger, gap, rate2, win, win2, mw; char order[40], stag[40]; };
const Tune g_tune = {-1500, 2460, 670, 220, 2600, 70, 70, 20, "abcKKKKKKKKVVVVVVVVOOxdefXYX", "8888888888888888888448888888"};
void make_schedule(Params& P, double speed) {
    const Tune& T = g_tune;
    int nk = 0, nv = 0, no = 0, nx = 0, n = 0, hist[40], hb[40], nh = 0;
    bool after = false;
    const double stagger = T.stagger / speed;
    double t = T.t0 + (T.stagger - stagger) / 2 + 31104 * 100.0 / (T.rate * speed);
    hb[nh] = T.mw * 1024; hist[nh++] = IT_M;
    for (const char* c = T.order; *c && n < NPOS; c++) {
        int item, bytes;
        switch (*c) {
            case 'a': case 'b': case 'c': item = IT_WQ + (*c - 'a'); bytes = 12288; break;
            case 'K': item = IT_K + nk++; bytes = 16384; break;
            case 'V': item = IT_V + nv++; bytes = 16384; break;
            case 'O': item = IT_WO + no++; bytes = 18432; break;
            case 'd': case 'e': case 'f': item = IT_W1 + (*c - 'd'); bytes = 12288; break;
            case 'X': item = IT_W2 + nx++; bytes = 18432; break;
            case 'x': item = IT_W1X; bytes = 4608; break;
            default: item = IT_W2C; bytes = 4608; break;
        }
        t += bytes * 100.0 / ((after ? T.rate2 : T.rate) * speed);
        int j = nh - 1, sum = bytes;
        while (j >= 0 && sum + hb[j] <= (after ? T.win2 : T.win) * 1024) sum += hb[j--];
        const int gate = j >= 0 ? hist[j] : IT_NONE;
        const int sg = T.stag[n] - '0';
        int tt = (int)(t + (8 - sg) * stagger / 16.0);
        tt = tt < 0 ? 0 : tt > 65535 ? 65535 : tt;
        P.sched[n++] = (uint32_t)item | (gate << 6) | (sg << 12) | ((uint32_t)tt << 16);
        if (bytes > 8192) { hb[nh] = bytes; hist[nh++] = item; }
        if (no == 2 && nv == 8 && !after) { after = true; t += T.gap; }
    }
    P.stagger = (uint32_t)stagger;
    P.probe_deadline = (uint32_t)(9300 / speed);
}

__device__ float f_a[FF], f_mod[6 * D], f_q[4096], f_x2[D], f_t[FF];
typedef const __nv_bfloat16* CB;
__device__ __forceinline__ float bf(CB p, size_t i) { return __bfloat162float(p[i]); }
__global__ void fb_gemv(const float* v, CB w, int K, int N, float* out) {
    const int n = blockIdx.x * blockDim.x + threadIdx.x;
    if (n >= N) return;
    float s = 0.f;
    for (int k = 0; k < K; k++) s += v[k] * bf(w, (size_t)k * N + n);
    out[n] = rb(s);
}
__device__ float fb_ln(float v, float* sh) {
    __syncthreads(); sh[threadIdx.x] = v; __syncthreads();
    float s = 0.f, q = 0.f;
    for (int i = 0; i < D; i++) s += sh[i];
    s /= D;
    for (int i = 0; i < D; i++) q += (sh[i] - s) * (sh[i] - s);
    return rb(rb(v - rb(s)) / rb(sqrtf(rb(rb(q / D) + 1e-5f))));
}
__global__ void fb_elem(int stage, CB x, CB c, CB b1, CB b2, __nv_bfloat16* out) {
    __shared__ float sh[D];
    const int i = threadIdx.x;
    if (stage == 0) { const float v = bf(c, i); f_a[i] = rb(v / (1.f + expf(-v))); }
    if (stage == 1) f_a[i] = rb(rb(fb_ln(bf(x, i), sh) * rb(1.f + f_mod[D + i])) + f_mod[i]);
    if (stage == 2) {
        f_x2[i] = rb(bf(x, i) + rb(f_mod[2 * D + i] * f_t[i]));
        f_a[i] = fb_ln(rb(rb(fb_ln(f_x2[i], sh) * rb(1.f + f_mod[4 * D + i])) + f_mod[3 * D + i]), sh);
    }
    if (stage == 3)
        for (int j = i; j < FF; j += D) {
            const float u = rb(f_t[j] + bf(b1, j));
            f_a[j] = rb(0.5f * u * (1.f + tanhf(0.7978845608028654f * (u + 0.044715f * u * u * u))));
        }
    if (stage == 4) out[i] = __float2bfloat16_rn(f_x2[i] + rb(f_mod[5 * D + i] * rb(f_t[i] + bf(b2, i))));
}
__global__ void fb_attn(CB k, CB v) {
    __shared__ float p[WIN], red[128];
    const int h = blockIdx.x, t = threadIdx.x;
    const size_t base = ((size_t)(h / 2) * SK + SK - WIN) * 128;
    float m = -INFINITY, l = 0.f, o = 0.f;
    for (int j = t; j < WIN; j += 128) {
        float s = 0.f;
        for (int d = 0; d < 128; d++) s += f_q[h * 128 + d] * bf(k, base + (size_t)j * 128 + d);
        p[j] = rb(rb(s) * 0.08838834764831845f);
        m = fmaxf(m, p[j]);
    }
    red[t] = m; __syncthreads();
    for (int i = 0; i < 128; i++) m = fmaxf(m, red[i]);
    __syncthreads();
    for (int j = t; j < WIN; j += 128) { p[j] = expf(p[j] - m); l += p[j]; }
    red[t] = l; __syncthreads();
    l = 0.f;
    for (int i = 0; i < 128; i++) l += red[i];
    for (int j = 0; j < WIN; j++) o += rb(p[j] / l) * bf(v, base + (size_t)j * 128 + t);
    f_a[h * 128 + t] = rb(o);
}
void fallback(void* const* in, void* out) {
    float *a, *mod, *q, *t;
    cudaGetSymbolAddress((void**)&a, f_a); cudaGetSymbolAddress((void**)&mod, f_mod);
    cudaGetSymbolAddress((void**)&q, f_q); cudaGetSymbolAddress((void**)&t, f_t);
#define ELEM(s) fb_elem<<<1, D>>>(s, (CB)in[0], (CB)in[10], (CB)in[7], (CB)in[9], (__nv_bfloat16*)out)
    ELEM(0); fb_gemv<<<54, 64>>>(a, (CB)in[11], D, 6 * D, mod);
    ELEM(1); fb_gemv<<<64, 64>>>(a, (CB)in[3], D, 4096, q);
    fb_attn<<<32, 128>>>((CB)in[1], (CB)in[2]); fb_gemv<<<9, 64>>>(a, (CB)in[4], 4096, D, t);
    ELEM(2); fb_gemv<<<72, 64>>>(a, (CB)in[6], D, FF, t);
    ELEM(3); fb_gemv<<<9, 64>>>(a, (CB)in[8], FF, D, t);
    ELEM(4);
#undef ELEM
}

}

extern "C" void kernel_launch(void* const* d_in, const int* in_sizes, int n_in, void* d_out, int out_size) {
    (void)in_sizes; (void)n_in; (void)out_size;
    int dev = 0, sms = 0, occ = 0, mclk = 0, bus = 0;
    cudaGetDevice(&dev);
    cudaDeviceGetAttribute(&sms, cudaDevAttrMultiProcessorCount, dev);
    cudaDeviceGetAttribute(&mclk, cudaDevAttrMemoryClockRate, dev);
    cudaDeviceGetAttribute(&bus, cudaDevAttrGlobalMemoryBusWidth, dev);
    cudaFuncSetAttribute(fused_kernel, cudaFuncAttributeMaxDynamicSharedMemorySize, SM_TOTAL);
    cudaOccupancyMaxActiveBlocksPerMultiprocessor(&occ, fused_kernel, NTHREADS, SM_TOTAL);
    void* fn = nullptr;
    cudaDriverEntryPointQueryResult qr;
    cudaGetDriverEntryPoint("cuTensorMapEncodeTiled", &fn, cudaEnableDefault, &qr);
    if (sms * occ < NATT || !fn) { (void)cudaGetLastError(); fallback(d_in, d_out); return; }
    EncodeFn enc = (EncodeFn)fn;

    Params P;
    make_map(enc, &P.m_wq, d_in[3], 4096, D, 32, 192, CU_TENSOR_MAP_SWIZZLE_64B, CU_TENSOR_MAP_L2_PROMOTION_L2_128B);
    make_map(enc, &P.m_k, d_in[1], 64, (uint64_t)HKV * SK * 2, 64, 128, CU_TENSOR_MAP_SWIZZLE_128B, CU_TENSOR_MAP_L2_PROMOTION_L2_256B);
    make_map(enc, &P.m_v, d_in[2], 64, (uint64_t)HKV * SK * 2, 64, 128, CU_TENSOR_MAP_SWIZZLE_128B, CU_TENSOR_MAP_L2_PROMOTION_L2_256B);
    make_map(enc, &P.m_wo, d_in[4], 64, 4096 * 9, 64, 144, CU_TENSOR_MAP_SWIZZLE_128B, CU_TENSOR_MAP_L2_PROMOTION_L2_256B);
    make_map(enc, &P.m_w1, d_in[6], FF, D, 32, 192, CU_TENSOR_MAP_SWIZZLE_64B, CU_TENSOR_MAP_L2_PROMOTION_L2_128B);
    make_map(enc, &P.m_w1x, d_in[6], FF, D, 16, 192, CU_TENSOR_MAP_SWIZZLE_NONE, CU_TENSOR_MAP_L2_PROMOTION_L2_64B);
    make_map(enc, &P.m_w2, d_in[8], 64, FF * 9, 64, 144, CU_TENSOR_MAP_SWIZZLE_128B, CU_TENSOR_MAP_L2_PROMOTION_L2_256B);
    P.b2 = (const __nv_bfloat16*)d_in[9];
    const double speed = mclk > 0 && bus > 0 ? (double)mclk * bus / (2619000.0 * 5120.0) : 1.0;
    make_schedule(P, speed);
    void* boxp = nullptr;
    cudaGetSymbolAddress(&boxp, g_box);
    uint4* box = (uint4*)(((uintptr_t)boxp + (2 << 20) - 1) & ~(uintptr_t)((2 << 20) - 1));
    fused_kernel<<<NATT, NTHREADS, SM_TOTAL>>>((const __nv_bfloat16*)d_in[11], (const __nv_bfloat16*)d_in[10], (const __nv_bfloat16*)d_in[0],
                                               box, (const __nv_bfloat16*)d_in[7], (__nv_bfloat16*)d_out, P);
}
```

```cpp
#include <cuda_runtime.h>
#include <cuda_bf16.h>
#include <cuda.h>
#include <stdint.h>

namespace {

constexpr int D = 576, HKV = 16, SK = 32768, WIN = 4096, FF = 4608;
constexpr int NATT = 128;
constexpr int NRED = 96;
constexpr int NMOD = 108;
constexpr int NCW = 12;
constexpr int NCT = NCW * 32;
constexpr int NTHREADS = NCT + 64;

constexpr int SM_K = 0;
constexpr int SM_WO = 0;
constexpr int SM_W2 = 36864;
constexpr int SM_W1 = 92160;
constexpr int SM_RING = 131072;
constexpr int SM_W1X = SM_RING + 3 * 16384;
constexpr int SM_M = SM_RING;
constexpr int SM_WQ = SM_RING + 36864;
constexpr int SM_MISC = SM_RING + 5 * 16384;
constexpr int SM_MOD = SM_MISC;
constexpr int SM_VEC = SM_MOD + 2304;
constexpr int SM_XN = SM_VEC + 1152;
constexpr int SM_Q = SM_XN + 1152;
constexpr int SM_S = SM_Q + 512;
constexpr int SM_P = SM_S + 4096;
constexpr int SM_RED = SM_P + 2048;
constexpr int SM_SMALL = SM_RED + 2304;
constexpr int SM_O = SM_SMALL + 256;
constexpr int SM_BAR = SM_O + 128;
constexpr int SM_TOTAL = SM_BAR + 40 * 8;
static_assert(SM_TOTAL <= 232448, "smem");

enum { IT_M = 0, IT_WQ = 1, IT_K = 4, IT_V = 12, IT_WO = 20, IT_W2 = 22, IT_W1 = 24, IT_W2C = 27, IT_W1X = 28,
       BF_WQ = 29, BF_K = 30, BF_X = 31, BF_V0 = 32  , NBAR_USED = 35, NPOS = 28, IT_NONE = 63 };

enum { BX_X2 = 0,
       BX_O = 1024,
       BX_PART = BX_O + NATT * 512,
       BX_MOD = BX_PART + NRED * 512,
       BX_Q = BX_MOD + 864,
       BX_ML = BX_Q + NATT * 8,
       BX_SIDE = BX_ML + NATT * 2,
       BX_EPOCH = BX_SIDE + 32,
       BX_TOTAL = BX_EPOCH + 8 };
static_assert(BX_TOTAL * 16 <= (2 << 20), "mailboxes stay inside one 2 MB page");
__device__ uint4 g_box[(4 << 20) / 16];
__device__ __forceinline__ uint32_t half_of(uint32_t pair, uint32_t side) {
    constexpr uint32_t MASK = ((1u << 13) | (1u << 16) | (1u << 17) | (1u << 19)) >> 4;
    return pair + (((__popc(pair & MASK) ^ side) & 1u) << 8);
}

constexpr unsigned SPIN_MAX = 1u << 20;
#define PIN(x) asm volatile("" : "+r"(x))

__device__ __forceinline__ uint32_t smem_u32(const void* p) { return (uint32_t)__cvta_generic_to_shared(p); }
__device__ __forceinline__ void mbar_init(uint32_t bar, uint32_t cnt) {
    asm volatile("mbarrier.init.shared::cta.b64 [%0], %1;" ::"r"(bar), "r"(cnt) : "memory");
}
__device__ __forceinline__ void mbar_expect_tx(uint32_t bar, uint32_t bytes) {
    asm volatile("mbarrier.arrive.expect_tx.shared::cta.b64 _, [%0], %1;" ::"r"(bar), "r"(bytes) : "memory");
}
__device__ __forceinline__ void mbar_arrive(uint32_t bar) {
    asm volatile("mbarrier.arrive.shared::cta.b64 _, [%0];" ::"r"(bar) : "memory");
}
__device__ __forceinline__ void mbar_wait(uint32_t bar) {
    uint32_t ok;
    unsigned n = 0;
#pragma unroll 1
    do {
        asm volatile("{\n.reg .pred p;\nmbarrier.try_wait.parity.shared::cta.b64 p, [%1], 0;\nselp.u32 %0, 1, 0, p;\n}"
                     : "=r"(ok) : "r"(bar) : "memory");
    } while (!ok && ++n < SPIN_MAX);
}
__device__ __forceinline__ bool mbar_done(uint32_t bar) {
    uint32_t ok;
    asm volatile("{\n.reg .pred p;\nmbarrier.test_wait.parity.shared::cta.b64 p, [%1], 0;\nselp.u32 %0, 1, 0, p;\n}"
                 : "=r"(ok) : "r"(bar) : "memory");
    return ok;
}
__device__ __forceinline__ bool mbar_test(uint32_t bar) { return __all_sync(0xffffffffu, mbar_done(bar)); }
__device__ __forceinline__ void tma2d(uint32_t dst, const CUtensorMap* map, int c0, int c1, uint32_t bar, uint64_t pol) {
    asm volatile("cp.async.bulk.tensor.2d.shared::cluster.global.mbarrier::complete_tx::bytes.L2::cache_hint [%0], [%1, {%3, %4}], [%2], %5;"
                 ::"r"(dst), "l"(map), "r"(bar), "r"(c0), "r"(c1), "l"(pol) : "memory");
}
__device__ __forceinline__ void cp16(uint32_t dst, const void* src, bool on) {
    asm volatile("{\n.reg .pred p;\nsetp.ne.u32 p, %2, 0;\n@p cp.async.cg.shared.global.L2::128B [%0], [%1], 16;\n}" ::"r"(dst), "l"(src), "r"((uint32_t)on) : "memory");
}
__device__ __forceinline__ void cp_arrive(uint32_t bar) {
    asm volatile("cp.async.mbarrier.arrive.noinc.shared::cta.b64 [%0];" ::"r"(bar) : "memory");
}
__device__ __forceinline__ void cbar() { asm volatile("bar.sync 1, %0;" ::"n"(NCT) : "memory"); }

__device__ __forceinline__ uint32_t lds32(uint32_t a) { uint32_t v; asm volatile("ld.shared.u32 %0, [%1];" : "=r"(v) : "r"(a) : "memory"); return v; }
__device__ __forceinline__ uint32_t lds16(uint32_t a) { uint32_t v; asm volatile("ld.shared.u16 %0, [%1];" : "=r"(v) : "r"(a) : "memory"); return v; }
__device__ __forceinline__ float ldsf(uint32_t a) { float v; asm volatile("ld.shared.f32 %0, [%1];" : "=f"(v) : "r"(a) : "memory"); return v; }
__device__ __forceinline__ float4 ldsf4(uint32_t a) {
    float4 v;
    asm volatile("ld.shared.v4.f32 {%0,%1,%2,%3}, [%4];" : "=f"(v.x), "=f"(v.y), "=f"(v.z), "=f"(v.w) : "r"(a) : "memory");
    return v;
}
__device__ __forceinline__ void sts32(uint32_t a, uint32_t v) { asm volatile("st.shared.u32 [%0], %1;" ::"r"(a), "r"(v) : "memory"); }
__device__ __forceinline__ void sts16(uint32_t a, uint32_t v) { asm volatile("st.shared.u16 [%0], %1;" ::"r"(a), "r"(v) : "memory"); }
__device__ __forceinline__ void stsf(uint32_t a, float v) { asm volatile("st.shared.f32 [%0], %1;" ::"r"(a), "f"(v) : "memory"); }
__device__ __forceinline__ void sts64(uint32_t a, uint32_t x, uint32_t y) { asm volatile("st.shared.v2.u32 [%0], {%1,%2};" ::"r"(a), "r"(x), "r"(y) : "memory"); }

__device__ __forceinline__ void st_msg(uint4* p, uint32_t a, uint32_t b, uint32_t c, uint32_t d) {
    asm volatile("{\n.reg .b128 t;\n.reg .b64 lo, hi;\nmov.b64 lo, {%1, %2};\nmov.b64 hi, {%3, %4};\nmov.b128 t, {lo, hi};\n"
                 "st.relaxed.gpu.global.b128 [%0], t;\n}" ::"l"(p), "r"(a), "r"(b), "r"(c), "r"(d) : "memory");
}
__device__ __forceinline__ uint4 ld_msg(const uint4* p) {
    uint4 v;
    asm volatile("{\n.reg .b128 t;\n.reg .b64 lo, hi;\nld.relaxed.gpu.global.b128 t, [%4];\nmov.b128 {lo, hi}, t;\n"
                 "mov.b64 {%0, %1}, lo;\nmov.b64 {%2, %3}, hi;\n}" : "=r"(v.x), "=r"(v.y), "=r"(v.z), "=r"(v.w) : "l"(p) : "memory");
    return v;
}
template <int BACKOFF = 0>
__device__ __forceinline__ uint4 poll_msg(const uint4* p, uint32_t tag) {
    uint4 v;
    v.w = tag + 1;
    unsigned n = 0;
#pragma unroll 1
    do {
        if (BACKOFF && n) __nanosleep(BACKOFF);
        if (v.w != tag) v = ld_msg(p);
    } while (__any_sync(0xffffffffu, v.w != tag) && ++n < SPIN_MAX);
    return v;
}
__device__ __forceinline__ void st_msg8(uint2* p, uint32_t a, uint32_t b) {
    asm volatile("{\n.reg .b64 t;\nmov.b64 t, {%1, %2};\nst.relaxed.gpu.global.b64 [%0], t;\n}" ::"l"(p), "r"(a), "r"(b) : "memory");
}
__device__ __forceinline__ uint2 ld_msg8(const uint2* p) {
    uint2 v;
    asm volatile("{\n.reg .b64 t;\nld.relaxed.gpu.global.b64 t, [%2];\nmov.b64 {%0, %1}, t;\n}" : "=r"(v.x), "=r"(v.y) : "l"(p) : "memory");
    return v;
}
__device__ __forceinline__ uint32_t ldg16(const __nv_bfloat16* p) {
    uint32_t v;
    asm volatile("ld.global.nc.u16 %0, [%1];" : "=r"(v) : "l"(p));
    return v;
}

__device__ __forceinline__ void ldsm4(uint32_t a, uint32_t* r) {
    asm volatile("ldmatrix.sync.aligned.m8n8.x4.shared.b16 {%0,%1,%2,%3}, [%4];" : "=r"(r[0]), "=r"(r[1]), "=r"(r[2]), "=r"(r[3]) : "r"(a) : "memory");
}
__device__ __forceinline__ void ldsm4t(uint32_t a, uint32_t* r) {
    asm volatile("ldmatrix.sync.aligned.m8n8.x4.trans.shared.b16 {%0,%1,%2,%3}, [%4];" : "=r"(r[0]), "=r"(r[1]), "=r"(r[2]), "=r"(r[3]) : "r"(a) : "memory");
}
__device__ __forceinline__ void ldsm2t(uint32_t a, uint32_t* r) {
    asm volatile("ldmatrix.sync.aligned.m8n8.x2.trans.shared.b16 {%0,%1}, [%2];" : "=r"(r[0]), "=r"(r[1]) : "r"(a) : "memory");
}
__device__ __forceinline__ void mma16(float* c, uint32_t a0, uint32_t a1, uint32_t a2, uint32_t a3, uint32_t b0, uint32_t b1) {
    asm volatile("mma.sync.aligned.m16n8k16.row.col.f32.bf16.bf16.f32 {%0,%1,%2,%3}, {%4,%5,%6,%7}, {%8,%9}, {%0,%1,%2,%3};"
                 : "+f"(c[0]), "+f"(c[1]), "+f"(c[2]), "+f"(c[3]) : "r"(a0), "r"(a1), "r"(a2), "r"(a3), "r"(b0), "r"(b1));
}

__device__ __forceinline__ uint32_t pack2(float lo, float hi) {
    uint32_t r;
    asm("cvt.rn.bf16x2.f32 %0, %1, %2;" : "=r"(r) : "f"(hi), "f"(lo));
    return r;
}
__device__ __forceinline__ float rb(float x) { return __uint_as_float(pack2(0.f, x)); }
__device__ __forceinline__ uint32_t f2b(float x) { return pack2(x, 0.f); }
__device__ __forceinline__ float blo(uint32_t u) { return __uint_as_float(u << 16); }
__device__ __forceinline__ float bhi(uint32_t u) { return __uint_as_float(u & 0xffff0000u); }
__device__ __forceinline__ float ex2(float x) { float r; asm("ex2.approx.ftz.f32 %0, %1;" : "=f"(r) : "f"(x)); return r; }
__device__ __forceinline__ float rcp(float x) { float r; asm("rcp.approx.ftz.f32 %0, %1;" : "=f"(r) : "f"(x)); return r; }
constexpr float LOG2E = 1.4426950408889634f;
__device__ __forceinline__ float sigm(float x) { return rcp(1.f + ex2(-LOG2E * x)); }

__device__ __forceinline__ float3 layernorm3(float3 v, uint32_t scr, uint32_t scr_w, int lane) {
    float s = v.x + v.y + v.z, q = v.x * v.x + v.y * v.y + v.z * v.z;
#pragma unroll
    for (int o = 16; o > 0; o >>= 1) {
        s += __shfl_xor_sync(0xffffffffu, s, o);
        q += __shfl_xor_sync(0xffffffffu, q, o);
    }
    if (lane == 0) sts64(scr_w, __float_as_uint(s), __float_as_uint(q));
    asm volatile("bar.sync 4, 192;" ::: "memory");
    const float4 e0 = ldsf4(scr), e1 = ldsf4(scr + 16), e2 = ldsf4(scr + 32);
    const float mean = ((e0.x + e0.z) + (e1.x + e1.z) + (e2.x + e2.z)) * (1.0f / D);
    const float var = ((e0.y + e0.w) + (e1.y + e1.w) + (e2.y + e2.w)) * (1.0f / D) - mean * mean;
    const float mb = rb(mean);
    float den;
    asm("sqrt.approx.ftz.f32 %0, %1;" : "=f"(den) : "f"(rb(rb(fmaxf(var, 0.f)) + 1e-5f)));
    const float inv = rcp(rb(den));
    return make_float3(rb(rb(v.x - mb) * inv), rb(rb(v.y - mb) * inv), rb(rb(v.z - mb) * inv));
}

template <int NT>
__device__ __forceinline__ void strip_load(uint32_t p4, uint32_t p2, int x, uint32_t (&b)[NT][6]) {
#pragma unroll
    for (int n = 0; n < NT; n++) {
        ldsm4t(p4 + ((n ^ x) << 4), &b[n][0]);
        ldsm2t(p2 + ((n ^ x) << 4), &b[n][4]);
    }
}
__device__ __forceinline__ float red_sum(uint32_t red_r) {
    cbar();
    float v[NCW];
#pragma unroll
    for (int w = 0; w < NCW; w++) v[w] = ldsf(red_r + w * 160);
    return ((v[0] + v[1]) + (v[2] + v[3])) + ((v[4] + v[5]) + (v[6] + v[7])) + ((v[8] + v[9]) + (v[10] + v[11]));
}
template <int NT>
__device__ __forceinline__ void strip_mma_store(const uint32_t (&a)[6], const uint32_t (&b)[NT][6], uint32_t red_w, int lane) {
    float c[NT][4];
#pragma unroll
    for (int n = 0; n < NT; n++) c[n][0] = c[n][1] = c[n][2] = c[n][3] = 0.f;
#pragma unroll
    for (int k = 0; k < 3; k++)
#pragma unroll
        for (int n = 0; n < NT; n++) mma16(c[n], a[2 * k], a[2 * k], a[2 * k + 1], a[2 * k + 1], b[n][2 * k], b[n][2 * k + 1]);
    if (lane < 4) {
#pragma unroll
        for (int n = 0; n < NT; n++) sts64(red_w + n * 32, __float_as_uint(c[n][0]), __float_as_uint(c[n][1]));
    }
}
template <int NT>
__device__ __forceinline__ float strip_mma(const uint32_t (&a)[6], const uint32_t (&b)[NT][6], uint32_t red_w, uint32_t red_r, int lane) {
    strip_mma_store<NT>(a, b, red_w, lane);
    return red_sum(red_r);
}

template <int N>
__device__ __forceinline__ void poll_slots(const uint4* p, uint32_t tag, uint4 (&v)[N]) {
    uint32_t pend = (1u << N) - 1;
    unsigned n = 0;
    bool more;
#pragma unroll 1
    do {
#pragma unroll
        for (int i = 0; i < N; i++) if (pend & (1u << i)) v[i] = ld_msg(p + i * 32);
        uint32_t x = 0;
#pragma unroll
        for (int i = 0; i < N; i++) x |= v[i].w ^ tag;
        more = __any_sync(0xffffffffu, x != 0);
        if (!more) break;
        pend = 0;
#pragma unroll
        for (int i = 0; i < N; i++) pend |= v[i].w != tag ? 1u << i : 0u;
    } while (++n < SPIN_MAX);
}
__device__ __forceinline__ float reduce_part(const uint4* p, uint32_t tag, int lane) {
    uint4 v[8];
    poll_slots<8>(p, tag, v);
#define F(i, c) __uint_as_float(v[i].c)
    float s0 = ((F(0, x) + F(1, x)) + (F(2, x) + F(3, x))) + ((F(4, x) + F(5, x)) + (F(6, x) + F(7, x)));
    float s1 = ((F(0, y) + F(1, y)) + (F(2, y) + F(3, y))) + ((F(4, y) + F(5, y)) + (F(6, y) + F(7, y)));
    float s2 = ((F(0, z) + F(1, z)) + (F(2, z) + F(3, z))) + ((F(4, z) + F(5, z)) + (F(6, z) + F(7, z)));
#undef F
#pragma unroll
    for (int o = 16; o > 1; o >>= 1) {
        s0 += __shfl_xor_sync(0xffffffffu, s0, o);
        s1 += __shfl_xor_sync(0xffffffffu, s1, o);
        s2 += __shfl_xor_sync(0xffffffffu, s2, o);
    }
    return lane < 2 ? s0 : lane < 4 ? s1 : s2;
}

struct Params {
    uint32_t sched[NPOS];
    uint16_t stagger, early;
    uint32_t probe_deadline;
    const __nv_bfloat16* b2;
    CUtensorMap m_wq, m_k, m_v, m_wo, m_w1, m_w2, m_w1x;
};

__global__ void __launch_bounds__(NTHREADS, 1)
fused_kernel(const __nv_bfloat16* __restrict__ p_wmod, const __nv_bfloat16* __restrict__ p_c, const __nv_bfloat16* __restrict__ p_x,
             uint4* const box, const __nv_bfloat16* __restrict__ p_b1, __nv_bfloat16* __restrict__ p_out,
             const __grid_constant__ Params P) {
    extern __shared__ __align__(1024) unsigned char smem[];
    uint32_t t_start;
    asm volatile("mov.u32 %0, %globaltimer_lo;" : "=r"(t_start));
    uint32_t tid = threadIdx.x, warp = tid >> 5, lane = tid & 31;
    uint32_t cta = blockIdx.x;
    const uint32_t sb = smem_u32(smem);
#define BAR(i) (sb + SM_BAR + (i) * 8)
    {
        const uint32_t row = warp * 48 + (lane >> 2);
        const char* src = reinterpret_cast<const char*>(p_wmod) + (row * (6 * D * 2) + cta * 64 + (lane & 3) * 16);
        const uint32_t d = sb + SM_M + row * 64 + (((lane & 3) ^ ((lane >> 3) & 3)) << 4);
#pragma unroll
        for (int k = 0; k < 6; k++) cp16(d + k * 512, src + k * 8 * (6 * D * 2), warp < NCW && cta < NMOD);
    }
    uint32_t grp = cta >> 3, rk = cta & 7;

    if (warp == NCW) {
        const uint32_t sc = P.sched[min(lane, NPOS - 1u)], stagger = P.stagger;
        const int i = sc & 31;
        int mapi = 1, c0 = 0, c1, bytes = 16384, fbar = -1;
        uint32_t dst;
        if (i < IT_K) {
            mapi = 0; c0 = cta * 32; c1 = (i - IT_WQ) * 192; dst = SM_WQ + (i - IT_WQ) * 12288; bytes = 12288;
        } else if (i < IT_WO) {
            const int k = (i - IT_K) & 7;
            c1 = (grp * SK + (SK - WIN) + ((k >> 1) * 16 + rk * 2 + (k & 1)) * 64) * 2;
            dst = SM_K + k * 16384;
            if (i >= IT_V) {
                mapi = 2; dst = SM_RING + (k < 5 ? k : k - 5) * 16384;
                fbar = k == 0 ? BF_WQ : k >= 5 ? BF_V0 + k - 5 : -1;
            }
        } else if (i < IT_W2) {
            mapi = 3; c1 = (grp * 256 + (i - IT_WO) * 128 + rk * 16) * 9; dst = SM_WO + (i - IT_WO) * 18432; bytes = 18432;
            fbar = BF_K;
        } else if (i < IT_W1) {
            mapi = 5; c1 = (cta * 32 + (i - IT_W2) * 16) * 9; dst = SM_W2 + (i - IT_W2) * 18432; bytes = 18432;
        } else if (i < IT_W2C) {
            mapi = 4; c0 = cta * 32; c1 = (i - IT_W1) * 192; dst = SM_W1 + (i - IT_W1) * 12288; bytes = 12288;
        } else if (i == IT_W2C) {
            mapi = 5; c1 = (4096 + (cta - NRED) * 16) * 9; dst = SM_W2 + 2 * 18432; bytes = cta >= NRED ? 18432 : 0;
        } else {
            mapi = 6; c0 = 4096 + (cta - NRED) * 16; c1 = 0; dst = SM_W1X; bytes = cta >= NRED ? 18432 : 0;
            fbar = BF_X;
        }
        uint64_t pol;
        asm volatile("createpolicy.fractional.L2::evict_first.b64 %0, 1.0;" : "=l"(pol));
        const uint32_t t_iss = t_start + (sc >> 17) * 2 + ((((sc >> 15) & 3) * ((cta + 32) & 127) * stagger) >> 8);
        const CUtensorMap* map = &P.m_wq + mapi;
        const uint32_t gates = ((sc >> 5) & 1023) | ((uint32_t)(fbar & 63) << 10), early = P.early;
        asm volatile("bar.sync 2, %0;" ::"n"(NTHREADS) : "memory");
#pragma unroll 1
        for (int k = cta >= NMOD ? 3 : 0; k < NPOS; k++) {
            const uint32_t gk = __shfl_sync(0xffffffffu, gates, k);
            const uint32_t tk = __shfl_sync(0xffffffffu, t_iss, k);
            if ((gk & 31) != 31) mbar_wait(BAR(gk & 31));
            if ((gk >> 10) != IT_NONE) mbar_wait(BAR(gk >> 10));
            uint32_t now;
            unsigned n = 0;
            do { asm volatile("mov.u32 %0, %globaltimer_lo;" : "=r"(now)); }
            while ((int)(now - tk) < 0 && !((int)(now + early - tk) >= 0 && mbar_done(BAR((gk >> 5) & 31))) && ++n < SPIN_MAX);
            if (lane == k && bytes) {
                const uint32_t bk = BAR(i);
                mbar_expect_tx(bk, bytes);
                tma2d(sb + dst, map, c0, c1, bk, pol);
                if (mapi == 6) { tma2d(sb + dst + 6144, map, c0, 192, bk, pol); tma2d(sb + dst + 12288, map, c0, 384, bk, pol); }
            }
            __syncwarp();
        }
        return;
    }

    if (warp > NCW) {
        if (lane == 0) {
#pragma unroll
            for (int i = 0; i < NBAR_USED; i++) mbar_init(BAR(i), i == IT_M ? NCT : i >= BF_X ? 4 : 1);
            asm volatile("fence.mbarrier_init.release.cluster;" ::: "memory");
        }
        __syncwarp();
        asm volatile("bar.arrive 2, %0;" ::"n"(NTHREADS) : "memory");
        if (lane == 0 && cta >= NMOD) {
            uint64_t pol;
            asm volatile("createpolicy.fractional.L2::evict_first.b64 %0, 1.0;" : "=l"(pol));
#pragma unroll
            for (int i = 0; i < 3; i++) {
                mbar_expect_tx(BAR(IT_WQ + i), 12288);
                tma2d(sb + SM_WQ + i * 12288, &P.m_wq, cta * 32, i * 192, BAR(IT_WQ + i), pol);
            }
        }
        __syncwarp();
        st_msg(box + half_of(BX_O + cta * 512, (lane >> 1) & 1) + 128 + (lane >> 2) * 16 + (lane & 1), 0u, 0u, 0u, 0u);
        uint32_t epoch;
        asm volatile("ld.relaxed.gpu.global.u32 %0, [%1];" : "=r"(epoch) : "l"(box + BX_EPOCH) : "memory");
        if (lane < 7) asm volatile("prefetch.tensormap [%0];" ::"l"(&P.m_wq + lane) : "memory");
        lane = __shfl_sync(0xffffffffu, lane, lane); cta = __shfl_sync(0xffffffffu, cta, 0);
        if (lane == 0) {
            uint32_t best0 = 0xffffffffu, best1 = 0xffffffffu, prev = 0;
            int wins = 0;
            bool clear = false;
#pragma unroll 1
            for (uint32_t r = 0; r < 80; r++) {
                uint32_t c0, c1 = 0;
                asm volatile("{\n.reg .pred p;\n.reg .u32 v;\nmov.u32 %0, %clock;\natom.relaxed.gpu.global.exch.b32 v, [%2], 0;\n"
                             "setp.ne.u32 p, v, 1;\n@p mov.u32 %1, %clock;\n}" : "=r"(c0), "+r"(c1)
                             : "l"(box + half_of(BX_O + cta * 512, r & 1) + 128 + ((r >> 1) & 7) * 16) : "memory");
                const uint32_t d = c1 - c0;
                if (r & 1) best1 = min(best1, d); else best0 = min(best0, d);
                if (r >= 3) wins += ((d < prev) == (r & 1)) ? 1 : -1;
                prev = d;
                const uint32_t lo = min(best0, best1), hi = max(best0, best1);
                clear = lo < 380 && lo * 10 < hi * 8;
                uint32_t now;
                asm volatile("mov.u32 %0, %globaltimer_lo;" : "=r"(now));
                if (r >= 3 && (clear || now - t_start > P.probe_deadline)) break;
            }
            uint32_t smid;
            asm volatile("mov.u32 %0, %smid;" : "=r"(smid));
            const uint32_t side = (clear || wins == 0) ? best1 < best0 : wins > 0;
            asm volatile("st.relaxed.gpu.global.u32 [%0], %1;" ::"l"(reinterpret_cast<uint32_t*>(box + BX_SIDE) + cta),
                         "r"(((epoch * 2 + 1) << 16) | ((smid >> 1) << 2) | (clear ? 2u : 0u) | side) : "memory");
        }
        __syncwarp();
        const uint32_t tag = epoch * 2 + 1;
        const uint32_t rcol = min(48 * (cta >> 3) + 8 * min(lane, 5u) + (cta & 7), D - 1u);
        const uint32_t rx = ldg16(p_x + rcol), rb2 = ldg16(P.b2 + rcol);
        const uint32_t rb1 = ldg16(p_b1 + cta * 32 + lane), rb1x = ldg16(p_b1 + 4096 + (cta & 31) * 16 + (lane & 15));
        __nv_bfloat16* const op = p_out + rcol;
        uint2* const x2_dst = reinterpret_cast<uint2*>(box + half_of(BX_X2 + ((lane >> 3) & 1) * 512, lane >> 1) + ((lane >> 2) & 1) * 128) +
                              (cta * 2 + (lane & 1));
        if (cta < NRED && lane < 16) st_msg8(x2_dst, 0u, 0u);
        mbar_wait(BAR(IT_K + 4));
        float ga, gb;
        {
            const uint4 va = poll_msg<200>(box + BX_MOD + (2 * D + rcol) / 4, tag), vb = poll_msg<200>(box + BX_MOD + (5 * D + rcol) / 4, tag);
            const uint32_t ua = rcol & 2 ? va.y : va.x, ub = rcol & 2 ? vb.y : vb.x;
            ga = rcol & 1 ? bhi(ua) : blo(ua);
            gb = rcol & 1 ? bhi(ub) : blo(ub);
        }
        asm volatile("bar.sync 3, %0;" ::"n"(NCT + 32) : "memory");
        const uint32_t side = lds32(sb + SM_XN + cta * 4);
        const uint4* part_src = box + (half_of(BX_PART + min(cta, NRED - 1u) * 512, side) + lane);
        {
            const uint4* src = box + (half_of(BX_O + cta * 512, side) + lane);
            mbar_wait(BAR(IT_V + 7));
            uint4 v[4];
            poll_slots<4>(src, tag, v);
            float o0 = (__uint_as_float(v[0].x) + __uint_as_float(v[1].x)) + (__uint_as_float(v[2].x) + __uint_as_float(v[3].x));
            float o1 = (__uint_as_float(v[0].y) + __uint_as_float(v[1].y)) + (__uint_as_float(v[2].y) + __uint_as_float(v[3].y));
            const float o = (lane < 16 ? o0 : o1) + __shfl_xor_sync(0xffffffffu, lane < 16 ? o1 : o0, 16);
            sts16(sb + SM_O + lane * 2, f2b(o));
            asm volatile("bar.arrive 10, %0;" ::"n"(NCT + 32) : "memory");
        }
        float r_x2 = 0.f;
        if (cta < NRED) {
            mbar_wait(BAR(IT_WO + 1));
            const float sv = reduce_part(part_src, tag, lane);
            r_x2 = rb(blo(rx) + rb(ga * rb(sv)));
            const uint32_t w = __float_as_uint(r_x2);
            const uint32_t w0 = __shfl_sync(0xffffffffu, w, lane & 1), w1 = __shfl_sync(0xffffffffu, w, (lane & 1) + 2),
                           w2 = __shfl_sync(0xffffffffu, w, (lane & 1) + 4);
            if (lane < 16) st_msg8(x2_dst, (w0 >> 16) | w1, (w2 >> 16) | (tag << 16));
            __syncwarp();
            asm volatile("bar.arrive 9, 224;" ::: "memory");
        }
        {
            asm volatile("bar.sync 8, %0;" ::"n"(NCT + 32) : "memory");
            uint32_t hv[2];
#pragma unroll
            for (int k = 0; k < 2; k++) {
                const uint32_t ra = sb + SM_RED + (k ? 32 + (lane & 15) : lane) * 48;
                const float4 p0 = ldsf4(ra), p1 = ldsf4(ra + 16), p2 = ldsf4(ra + 32);
                const float r = ((p0.x + p0.y) + (p0.z + p0.w)) + ((p1.x + p1.y) + (p1.z + p1.w)) + ((p2.x + p2.y) + (p2.z + p2.w));
                const float u = rb(rb(r) + blo(k ? rb1x : rb1));
                const float z = 1.5957691216057308f * (u + 0.044715f * u * u * u);
                hv[k] = f2b(u * sigm(z));
            }
            sts16(sb + SM_O + lane * 2, hv[0]);
            if (lane < 16) sts16(sb + SM_O + 64 + lane * 2, hv[1]);
            __syncwarp();
            asm volatile("bar.arrive 6, %0;" ::"n"(NCT + 32) : "memory");
        }
        if (cta < NRED) {
            mbar_wait(BAR(IT_W2 + 1));
            const float sv = reduce_part(part_src, tag + 1, lane);
            const uint32_t y = f2b(r_x2 + rb(gb * rb(rb(sv) + blo(rb2))));
            if (lane < 6) asm volatile("st.global.u16 [%0], %1;" ::"l"(op), "r"(y) : "memory");
            if (cta == 0 && lane == 0) asm volatile("st.relaxed.gpu.global.u32 [%0], %1;" ::"l"(box + BX_EPOCH), "r"(epoch + 1) : "memory");
        }
        return;
    }

    tid = __shfl_sync(0xffffffffu, tid, lane); cta = __shfl_sync(0xffffffffu, cta, 0);
    warp = tid >> 5; lane = tid & 31; grp = cta >> 3; rk = cta & 7;
    const uint32_t t = lane & 3, gq = lane >> 2;
    const uint32_t li = tid - 64;
    const bool is_ln = li < 192;
    const uint32_t lcol = is_ln ? 48 * (li >> 4) + 8 * (li & 1) + ((li >> 1) & 7) : 0;
    const uint32_t vi = warp * 24 + min(lane, 23u);
    uint32_t cv = 0, epoch = 0, x0 = 0, x1 = 0, x2 = 0;
    if (cta < NMOD) asm volatile("ld.global.nc.u32 %0, [%1];" : "=r"(cv) : "l"(reinterpret_cast<const uint32_t*>(p_c) + vi));
    if (warp == 0) asm volatile("ld.relaxed.gpu.global.u32 %0, [%1];" : "=r"(epoch) : "l"(box + BX_EPOCH) : "memory");
    if (is_ln) { x0 = ldg16(p_x + li); x1 = ldg16(p_x + li + 192); x2 = ldg16(p_x + li + 384); }
    asm volatile("cp.async.commit_group;" ::: "memory");
    asm volatile("bar.sync 2, %0;" ::"n"(NTHREADS) : "memory");
    cp_arrive(BAR(IT_M));
    if (warp == 8) {
        const uint32_t idx = lane < 8 ? BX_MOD + cta * 8 + lane : lane < 16 ? BX_Q + cta * 8 + lane - 8 : BX_ML + cta * 2 + lane - 16;
        if (lane < 18 && (lane >= 8 || cta < NMOD)) st_msg(box + idx, 0u, 0u, 0u, 0u);
    }
    uint32_t a[6];
    {
        PIN(cv);
        const float c0 = blo(cv), c1 = bhi(cv);
        const uint32_t av = pack2(c0 * sigm(c0), c1 * sigm(c1));
#pragma unroll
        for (int i = 0; i < 6; i++) a[i] = __shfl_sync(0xffffffffu, av, i * 4 + t);
    }
    const uint32_t scr_w = sb + SM_SMALL + (warp - 2) * 8;
    PIN(x0); PIN(x1); PIN(x2);
    if (is_ln) {
        const float3 xv = layernorm3(make_float3(blo(x0), blo(x1), blo(x2)), sb + SM_SMALL + 192, scr_w + 192, lane);
        sts16(sb + SM_XN + li * 2, __float_as_uint(xv.x) >> 16);
        sts16(sb + SM_XN + li * 2 + 384, __float_as_uint(xv.y) >> 16);
        sts16(sb + SM_XN + li * 2 + 768, __float_as_uint(xv.z) >> 16);
    }
    uint32_t tag = epoch * 2 + 1;
    if (tid == 0) sts32(sb + SM_O + 124, tag);
    const uint32_t red_w = sb + SM_RED + warp * 160 + lane * 8, red_r = sb + SM_RED + min(tid, 39u) * 4;
    const uint32_t r4 = warp * 48 + lane, r2 = warp * 48 + 32 + (lane & 15);

    asm volatile("cp.async.wait_group 0;" ::: "memory");
    asm volatile("fence.proxy.async.shared::cta;" ::: "memory");
    __syncwarp();
    const bool extra = cta >= NRED;
    const uint32_t w1row = warp * 48 + (lane & 7) + 8 * (lane >> 4);
#pragma unroll 1
    for (uint32_t ph = cta < NMOD ? 0 : 1; ph < 2; ph++) {
        if (ph) {
            cbar();
            tag = lds32(sb + SM_O + 124);
            const uint32_t l24 = min(lane, 23u), sl = (l24 >= 12 ? 132 : 0) + warp * 12 + l24;
            mbar_wait(BAR(IT_WQ + 1));
            const uint4 v = poll_msg<250>(box + BX_MOD + sl, tag);
            sts64(sb + SM_MOD + sl * 8, v.x, v.y);
            __syncwarp();
            const uint32_t xn = lds32(sb + SM_XN + vi * 4), sa = lds32(sb + SM_MOD + vi * 4), ca = lds32(sb + SM_MOD + 1152 + vi * 4);
            const uint32_t one = pack2(1.f + blo(ca), 1.f + bhi(ca));
            const uint32_t pr = pack2(blo(xn) * blo(one), bhi(xn) * bhi(one));
            const uint32_t av = pack2(blo(pr) + blo(sa), bhi(pr) + bhi(sa));
#pragma unroll
            for (int i = 0; i < 6; i++) a[i] = __shfl_sync(0xffffffffu, av, i * 4 + t);
            mbar_wait(BAR(IT_WQ + (warp >> 2)));
        }
        uint32_t b[4][6];
        strip_load<4>(sb + SM_M + ph * 36864 + r4 * 64, sb + SM_M + ph * 36864 + r2 * 64, (lane >> 1) & 3, b);
        const float r = strip_mma<4>(a, b, red_w, red_r, lane);
        if (warp == 0) {
            sts16(sb + SM_O + lane * 2, f2b(r));
            __syncwarp();
            if (lane < 8) st_msg(box + (ph ? BX_Q : BX_MOD) + cta * 8 + lane, lds32(sb + SM_O + lane * 8), lds32(sb + SM_O + lane * 8 + 4), 0u, tag);
        }
    }
    if (tid == 0) mbar_arrive(BAR(BF_WQ));
    if (li < 64) {
        const uint4 v = poll_msg<200>(box + BX_Q + grp * 64 + li, tag);
        sts64(sb + SM_Q + li * 8, v.x, v.y);
    }
    cbar();
    const uint32_t ob = sb + SM_O + t * 4;

    if (warp < 8) {
        uint32_t bq[4][2];
        const uint32_t msk = gq < 4 ? 0xffffffffu : 0u;
#pragma unroll
        for (int ks = 0; ks < 4; ks++) {
            const uint32_t qa = sb + SM_Q + ((gq & 1) * 64 + (gq & 2) * 16 + ks * 8 + t) * 4;
            bq[ks][0] = lds32(qa) & msk;
            bq[ks][1] = lds32(qa + 16) & msk;
        }
        float mx0 = -INFINITY, mx1 = -INFINITY;
        uint32_t rowaddr = sb + SM_K + (warp * 16 + (lane & 15)) * 128;
        const uint32_t xo = (lane >> 4) ^ (lane & 7);
        uint32_t sa = sb + SM_S + (warp * 8 + (lane >> 3)) * 4;
#pragma unroll 1
        for (int ch = 0; ch < 8; ch += 2) {
            uint32_t ka[2][4][4];
#pragma unroll
            for (int u = 0; u < 2; u++) {
                mbar_wait(BAR(IT_K + ch + u));
#pragma unroll
                for (int ks = 0; ks < 4; ks++) ldsm4(rowaddr + u * 16384 + (((2 * ks) ^ xo) << 4), ka[u][ks]);
            }
            float c[2][4];
#pragma unroll
            for (int u = 0; u < 2; u++) c[u][0] = c[u][1] = c[u][2] = c[u][3] = 0.f;
#pragma unroll
            for (int ks = 0; ks < 4; ks++)
#pragma unroll
                for (int u = 0; u < 2; u++)
                    mma16(c[u], ka[u][ks][0], ka[u][ks][1], ka[u][ks][2], ka[u][ks][3], bq[ks][0], bq[ks][1]);
            const float sc = 0.08838834764831845f;
#pragma unroll
            for (int u = 0; u < 2; u++) {
#pragma unroll
                for (int i = 0; i < 4; i++) c[u][i] = rb(rb(c[u][i] + __shfl_down_sync(0xffffffffu, c[u][i], 5)) * sc);
                if ((lane & 7) == 0) {
                    const uint32_t d = sa + u * 256;
                    stsf(d, c[u][0]); stsf(d + 2048, c[u][1]); stsf(d + 16, c[u][2]); stsf(d + 2064, c[u][3]);
                }
                mx0 = fmaxf(mx0, fmaxf(c[u][0], c[u][2]));
                mx1 = fmaxf(mx1, fmaxf(c[u][1], c[u][3]));
            }
            rowaddr += 32768; sa += 512;
        }
#pragma unroll
        for (int o = 8; o <= 16; o <<= 1) {
            mx0 = fmaxf(mx0, __shfl_xor_sync(0xffffffffu, mx0, o));
            mx1 = fmaxf(mx1, __shfl_xor_sync(0xffffffffu, mx1, o));
        }
        if (lane == 0) { stsf(sb + SM_SMALL + warp * 4, mx0); stsf(sb + SM_SMALL + 32 + warp * 4, mx1); }
        asm volatile("bar.sync 5, 256;" ::: "memory");
        if (tid == 0) mbar_arrive(BAR(BF_K));
        const uint32_t hd = warp >> 2;
        const float4 ma = ldsf4(sb + SM_SMALL + hd * 32), mb = ldsf4(sb + SM_SMALL + hd * 32 + 16);
        const float4 s4 = ldsf4(sb + SM_S + tid * 16);
        const float m = fmaxf(fmaxf(fmaxf(ma.x, ma.y), fmaxf(ma.z, ma.w)), fmaxf(fmaxf(mb.x, mb.y), fmaxf(mb.z, mb.w)));
        const float p0 = ex2((s4.x - m) * LOG2E), p1 = ex2((s4.y - m) * LOG2E), p2 = ex2((s4.z - m) * LOG2E), p3 = ex2((s4.w - m) * LOG2E);
        sts64(sb + SM_P + tid * 8, pack2(p0, p1), pack2(p2, p3));
        float l = (p0 + p1) + (p2 + p3);
#pragma unroll
        for (int o = 16; o > 0; o >>= 1) l += __shfl_xor_sync(0xffffffffu, l, o);
        if (lane == 0) { stsf(sb + SM_SMALL + 128 + warp * 4, l); stsf(sb + SM_SMALL + 160 + hd * 4, m); }
        asm volatile("bar.sync 5, 256;" ::: "memory");
    }

    uint32_t wad[3];
#pragma unroll
    for (int i = 0; i < 3; i++) {
        const uint32_t T = warp * 3 + i, blk = T >> 2, ch = 2 * (T & 3) + ((lane >> 3) & 1);
        const uint32_t fr = ((lane & 7) + 8 * (lane >> 4)) * 9 + blk;
        wad[i] = sb + fr * 128 + ((ch ^ (fr & 7)) << 4);
        PIN(wad[i]);
    }
    if (warp < 4) {
        float c[2][4];
#pragma unroll
        for (int i = 0; i < 2; i++) c[i][0] = c[i][1] = c[i][2] = c[i][3] = 0.f;
        const uint32_t row = (lane & 7) + 8 * (lane >> 4);
        const uint32_t off = sb + SM_RING + row * 128 + (((2 * warp + ((lane >> 3) & 1)) ^ (lane & 7)) << 4);
        uint32_t pp = sb + SM_P + ((gq & 1) * 512 + t) * 2;
        const uint32_t mul = gq < 2 ? 1u : gq < 4 ? 65536u : 0u;
        float f0 = 0.f, f1 = 0.f;
        uint4* o_dst = box;
        uint32_t slot = 0;
#pragma unroll 1
        for (int ch = 0; ch < 8; ch++) {
            uint32_t bp[16];
#pragma unroll
            for (int i = 0; i < 16; i++) bp[i] = lds16(pp + i * 8) * mul;
            if (ch == 7) {
                asm volatile("bar.sync 3, %0;" ::"n"(NCT + 32) : "memory");
                f0 = ldsf(sb + SM_SMALL + 176); f1 = ldsf(sb + SM_SMALL + 180);
                const uint32_t ro = grp * 8 + (t & 1) * 4 + warp;
                o_dst = box + (half_of(BX_O + ro * 512, lds32(sb + SM_XN + ro * 4)) + rk * 16 + gq);
            }
            uint32_t base = off + slot * 16384;
            PIN(base);
            mbar_wait(BAR(IT_V + ch));
            uint32_t va[8][4];
#pragma unroll
            for (int ks = 0; ks < 8; ks++) ldsm4t(base + ks * 2048, va[ks]);
#pragma unroll
            for (int ks = 0; ks < 8; ks++) mma16(c[ks & 1], va[ks][0], va[ks][1], va[ks][2], va[ks][3], bp[2 * ks], bp[2 * ks + 1]);
            if ((ch < 3 || ch == 4) && lane == 0) mbar_arrive(BAR(ch == 4 ? BF_X : BF_V0 + ch));
            slot = slot == 4 ? 0 : slot + 1;
            pp += 128;
        }
        if (t < 2) {
            st_msg(o_dst, __float_as_uint((c[0][0] + c[1][0]) * f0), __float_as_uint((c[0][1] + c[1][1]) * f1), 0u, tag);
            st_msg(o_dst + 8, __float_as_uint((c[0][2] + c[1][2]) * f0), __float_as_uint((c[0][3] + c[1][3]) * f1), 0u, tag);
        }
    } else {
        if (warp == 4) {
            const uint32_t hd = lane & 1;
            const float m_own = ldsf(sb + SM_SMALL + 160 + hd * 4);
            const float4 l4 = ldsf4(sb + SM_SMALL + 128 + hd * 16);
            if (lane < 2) st_msg(box + BX_ML + cta * 2 + lane, __float_as_uint(m_own), __float_as_uint((l4.x + l4.y) + (l4.z + l4.w)), 0u, tag);
            mbar_wait(BAR(IT_V + 3));
            const uint4 v = poll_msg<300>(box + BX_ML + grp * 16 + (lane & 15), tag);
            const float ms = __uint_as_float(v.x);
            float M = ms;
#pragma unroll
            for (int o = 2; o <= 8; o <<= 1) M = fmaxf(M, __shfl_xor_sync(0xffffffffu, M, o));
            float L = __uint_as_float(v.y) * ex2((ms - M) * LOG2E);
#pragma unroll
            for (int o = 2; o <= 8; o <<= 1) L += __shfl_xor_sync(0xffffffffu, L, o);
            if (lane < 2) stsf(sb + SM_SMALL + 176 + lane * 4, ex2((m_own - M) * LOG2E) * rcp(L));
        } else if (warp >= 8) {
#pragma unroll 1
            for (uint32_t i = tid - 256; i < 288; i += 128) {
                const uint4 v = poll_msg<200>(box + BX_MOD + 432 + i, tag);
                sts64(sb + SM_MOD + i * 8, v.x, v.y);
            }
            mbar_wait(BAR(IT_V + 2));
            const uint32_t u = tid - 256;
            const uint32_t* side = reinterpret_cast<const uint32_t*>(box + BX_SIDE) + u;
            uint32_t sp;
            unsigned n = 0;
#pragma unroll 1
            do {
                if (n) __nanosleep(500);
                asm volatile("ld.relaxed.gpu.global.u32 %0, [%1];" : "=r"(sp) : "l"(side) : "memory");
            } while (__any_sync(0xffffffffu, (sp >> 16) != (tag & 0xffffu)) && ++n < SPIN_MAX);
            const uint32_t nb = __shfl_xor_sync(0xffffffffu, sp, 1);
            sts32(sb + SM_XN + u * 4, (((sp ^ nb) >> 1) == 1 && (nb & 2) ? nb : sp) & 1);
            asm volatile("bar.sync 7, 128;" ::: "memory");
#pragma unroll
            for (int k = 0; k < 2; k++) {
                const uint32_t rp = k * 64 + (u >> 1);
                if (rp < NRED) st_msg(box + (half_of(BX_PART + rp * 512, lds32(sb + SM_XN + rp * 4)) + cta * 2 + (u & 1)), 0u, 0u, 0u, 0u);
            }
            const uint32_t ro = grp * 8 + (u >> 4);
            st_msg(box + (half_of(BX_O + ro * 512, lds32(sb + SM_XN + ro * 4)) + rk * 16 + (u & 15)), 0u, 0u, 0u, 0u);
            asm volatile("bar.arrive 3, %0;" ::"n"(NCT + 32) : "memory");
        }
        if (warp < 8) asm volatile("bar.sync 3, %0;" ::"n"(NCT + 32) : "memory");
    }

    uint4* const part_dst = box + (half_of(BX_PART + (warp * 8 + gq) * 512, lds32(sb + SM_XN + (warp * 8 + gq) * 4)) + cta * 2 + (t & 1));
    const uint32_t my_side = lds32(sb + SM_XN + cta * 4);
    {
        uint32_t wa[3][8];
        mbar_wait(BAR(IT_WO));
#pragma unroll
        for (int i = 0; i < 3; i++) ldsm4t(wad[i] + SM_WO, &wa[i][0]);
        const bool pre0 = mbar_test(BAR(IT_WO + 1));
        if (pre0) {
#pragma unroll
            for (int i = 0; i < 3; i++) ldsm4t(wad[i] + SM_WO + 16 * 1152, &wa[i][4]);
        }
        asm volatile("bar.sync 10, %0;" ::"n"(NCT + 32) : "memory");
        const uint32_t b0 = lds32(ob), b1 = lds32(ob + 16), b2 = lds32(ob + 32), b3 = lds32(ob + 48);
        float c[3][4];
#pragma unroll
        for (int i = 0; i < 3; i++) {
            c[i][0] = c[i][1] = c[i][2] = c[i][3] = 0.f;
            mma16(c[i], wa[i][0], wa[i][1], wa[i][2], wa[i][3], b0, b1);
        }
        if (!pre0) {
            mbar_wait(BAR(IT_WO + 1));
#pragma unroll
            for (int i = 0; i < 3; i++) ldsm4t(wad[i] + SM_WO + 16 * 1152, &wa[i][4]);
        }
#pragma unroll
        for (int i = 0; i < 3; i++) mma16(c[i], wa[i][4], wa[i][5], wa[i][6], wa[i][7], b2, b3);
        if (t < 2) st_msg(part_dst, __float_as_uint(t ? c[0][2] : c[0][0]), __float_as_uint(t ? c[1][2] : c[1][0]),
                          __float_as_uint(t ? c[2][2] : c[2][0]), tag);
    }
    uint32_t wb[6][4], wx[3][4];
    const uint32_t w1bar = BAR((lane & 1) && extra ? IT_W1X : IT_W1 + (warp >> 2));
    const uint32_t w1a = sb + SM_W1 + w1row * 64 + ((((lane >> 3) & 1) ^ ((lane >> 1) & 3)) << 4);
    const uint32_t w1x = sb + SM_W1X + w1row * 32 + ((lane >> 3) & 1) * 16;
#define W1_LOAD() do { _Pragma("unroll") for (int k = 0; k < 3; k++) { \
        if (extra) ldsm4t(w1x + k * 512, wx[k]); \
        ldsm4t(w1a + k * 1024, wb[k * 2]); ldsm4t((w1a ^ 32) + k * 1024, wb[k * 2 + 1]); } } while (0)
    bool pre1 = false;
    if (is_ln) {
        const uint32_t ma = sb + SM_MOD + lcol * 2;
        float c0 = rb(1.f + blo(lds16(ma + 2 * D))), c1 = rb(1.f + blo(lds16(ma + 2 * D + 32))), c2 = rb(1.f + blo(lds16(ma + 2 * D + 64)));
        float s0 = blo(lds16(ma)), s1 = blo(lds16(ma + 32)), s2 = blo(lds16(ma + 64));
        const uint2* src = reinterpret_cast<const uint2*>(box + half_of(BX_X2 + (cta & 2) * 256, my_side) + (cta & 1) * 128) + li;
        const uint32_t yd = sb + SM_VEC + lcol * 2;
        uint2 v;
        bool xp = true;
        unsigned n = 0;
        if (cta < NRED) asm volatile("bar.sync 9, 224;" ::: "memory");
        else mbar_wait(w1bar);
        pre1 = mbar_test(w1bar);
        if (pre1) W1_LOAD();
#pragma unroll 1
        do { if (xp) v = ld_msg8(src); xp = (v.y >> 16) != (tag & 0xffffu); } while (__any_sync(0xffffffffu, xp) && ++n < SPIN_MAX);
        float3 y = layernorm3(make_float3(blo(v.x), bhi(v.x), blo(v.y)), sb + SM_SMALL, scr_w, lane);
        y = layernorm3(make_float3(rb(rb(y.x * c0) + s0), rb(rb(y.y * c1) + s1), rb(rb(y.z * c2) + s2)), sb + SM_SMALL + 64, scr_w + 64, lane);
        sts16(yd, __float_as_uint(y.x) >> 16); sts16(yd + 32, __float_as_uint(y.y) >> 16); sts16(yd + 64, __float_as_uint(y.z) >> 16);
    }
    {
        const uint32_t ya = sb + SM_VEC + (warp * 24 + t) * 4;
        const uint32_t rd = sb + SM_RED + (t * 16 + gq) * 48 + warp * 4;
        if (!pre1) {
            mbar_wait(w1bar);
            __syncwarp();
            W1_LOAD();
        }
        cbar();
#pragma unroll
        for (int i = 0; i < 6; i++) a[i] = lds32(ya + i * 16);
        float c[3][4];
#pragma unroll
        for (int j = 0; j < 3; j++) c[j][0] = c[j][1] = c[j][2] = c[j][3] = 0.f;
#pragma unroll
        for (int k = 0; k < 3; k++) {
#pragma unroll
            for (int j = 0; j < 2; j++) mma16(c[j], wb[k * 2 + j][0], wb[k * 2 + j][1], wb[k * 2 + j][2], wb[k * 2 + j][3], a[2 * k], a[2 * k + 1]);
            if (extra) mma16(c[2], wx[k][0], wx[k][1], wx[k][2], wx[k][3], a[2 * k], a[2 * k + 1]);
        }
        if (t < 3) {
            stsf(rd, t == 0 ? c[0][0] : t == 1 ? c[1][0] : c[2][0]);
            stsf(rd + 8 * 48, t == 0 ? c[0][2] : t == 1 ? c[1][2] : c[2][2]);
        }
        asm volatile("bar.arrive 8, %0;" ::"n"(NCT + 32) : "memory");
    }
    {
        uint32_t wa[3][12];
        mbar_wait(BAR((lane & 1) && extra ? IT_W2C : IT_W2));
        __syncwarp();
#pragma unroll
        for (int i = 0; i < 3; i++) {
            ldsm4t(wad[i] + SM_W2, &wa[i][0]);
            if (extra) ldsm4t(wad[i] + SM_W2 + 32 * 1152, &wa[i][8]);
        }
        const bool pre = mbar_test(BAR(IT_W2 + 1));
        if (pre) {
#pragma unroll
            for (int i = 0; i < 3; i++) ldsm4t(wad[i] + SM_W2 + 16 * 1152, &wa[i][4]);
        }
        asm volatile("bar.sync 6, %0;" ::"n"(NCT + 32) : "memory");
        uint32_t b[6];
#pragma unroll
        for (int i = 0; i < 6; i++) b[i] = lds32(ob + i * 16);
        float c[3][4], e[3][4], f[3][4];
#pragma unroll
        for (int i = 0; i < 3; i++) {
#pragma unroll
            for (int j = 0; j < 4; j++) c[i][j] = e[i][j] = f[i][j] = 0.f;
            mma16(c[i], wa[i][0], wa[i][1], wa[i][2], wa[i][3], b[0], b[1]);
            if (extra) mma16(e[i], wa[i][8], wa[i][9], wa[i][10], wa[i][11], b[4], b[5]);
        }
        if (!pre) {
            mbar_wait(BAR(IT_W2 + 1));
#pragma unroll
            for (int i = 0; i < 3; i++) ldsm4t(wad[i] + SM_W2 + 16 * 1152, &wa[i][4]);
        }
#pragma unroll
        for (int i = 0; i < 3; i++) mma16(f[i], wa[i][4], wa[i][5], wa[i][6], wa[i][7], b[2], b[3]);
        float r[3];
#pragma unroll
        for (int i = 0; i < 3; i++) r[i] = t ? (c[i][2] + e[i][2]) + f[i][2] : (c[i][0] + e[i][0]) + f[i][0];
        if (t < 2) st_msg(part_dst, __float_as_uint(r[0]), __float_as_uint(r[1]), __float_as_uint(r[2]), tag + 1);
    }
#undef BAR
}

typedef CUresult (*EncodeFn)(CUtensorMap*, CUtensorMapDataType, cuuint32_t, void*, const cuuint64_t*, const cuuint64_t*,
                             const cuuint32_t*, const cuuint32_t*, CUtensorMapInterleave, CUtensorMapSwizzle,
                             CUtensorMapL2promotion, CUtensorMapFloatOOBfill);

void make_map(EncodeFn enc, CUtensorMap* m, const void* base, uint64_t cols, uint64_t rows, uint32_t bc, uint32_t br,
              CUtensorMapSwizzle sw, CUtensorMapL2promotion promo) {
    cuuint64_t dims[2] = {cols, rows};
    cuuint64_t strides[1] = {cols * 2};
    cuuint32_t box[2] = {bc, br};
    cuuint32_t es[2] = {1, 1};
    enc(m, CU_TENSOR_MAP_DATA_TYPE_BFLOAT16, 2, const_cast<void*>(base), dims, strides, box, es,
        CU_TENSOR_MAP_INTERLEAVE_NONE, sw, promo, CU_TENSOR_MAP_FLOAT_OOB_FILL_NONE);
}

struct Tune { int t0, rate, stagger, gap, rate2, win, win2, mw; char order[40], stag[40]; };
const Tune g_tune = {-1470, 2460, 670, 220, 2600, 70, 70, 20, "abcKKKKKKKKVVVVVVVVOOxdefXYX", "8888888888888888888448888888"};
void make_schedule(Params& P, double speed) {
    const Tune& T = g_tune;
    int nk = 0, nv = 0, no = 0, nx = 0, n = 0, hist[40], hb[40], nh = 0;
    bool after = false;
    const double stagger = T.stagger / speed;
    double t = T.t0 + (T.stagger - stagger) / 2 + 31104 * 100.0 / (T.rate * speed);
    hb[nh] = T.mw * 1024; hist[nh++] = IT_M;
    for (const char* c = T.order; *c && n < NPOS; c++) {
        int item, bytes;
        switch (*c) {
            case 'a': case 'b': case 'c': item = IT_WQ + (*c - 'a'); bytes = 12288; break;
            case 'K': item = IT_K + nk++; bytes = 16384; break;
            case 'V': item = IT_V + nv++; bytes = 16384; break;
            case 'O': item = IT_WO + no++; bytes = 18432; break;
            case 'd': case 'e': case 'f': item = IT_W1 + (*c - 'd'); bytes = 12288; break;
            case 'X': item = IT_W2 + nx++; bytes = 18432; break;
            case 'x': item = IT_W1X; bytes = 4608; break;
            default: item = IT_W2C; bytes = 4608; break;
        }
        t += bytes * 100.0 / ((after ? T.rate2 : T.rate) * speed);
        int j = nh - 1, sum = bytes;
        while (j >= 0 && sum + hb[j] <= (after ? T.win2 : T.win) * 1024) sum += hb[j--];
        const int gate = j >= 0 ? hist[j] : 31, gate2 = hist[nh >= 2 ? nh - 2 : 0];
        const int sg = T.stag[n] - '0';
        int tt = (int)(t + (8 - sg) * stagger / 16.0);
        tt = tt < 0 ? 0 : tt > 65535 ? 65535 : tt;
        P.sched[n++] = (uint32_t)item | (gate << 5) | (gate2 << 10) | ((sg / 4) << 15) | ((uint32_t)(tt / 2) << 17);
        if (bytes > 8192) { hb[nh] = bytes; hist[nh++] = item; }
        if (no == 2 && nv == 8 && !after) { after = true; t += T.gap; }
    }
    P.stagger = (uint16_t)stagger;
    P.early = 200;
    P.probe_deadline = (uint32_t)(9300 / speed);
}

__device__ float f_a[FF], f_mod[6 * D], f_q[4096], f_x2[D], f_t[FF];
typedef const __nv_bfloat16* CB;
__device__ __forceinline__ float bf(CB p, size_t i) { return __bfloat162float(p[i]); }
__global__ void fb_gemv(const float* v, CB w, int K, int N, float* out) {
    const int n = blockIdx.x * blockDim.x + threadIdx.x;
    if (n >= N) return;
    float s = 0.f;
    for (int k = 0; k < K; k++) s += v[k] * bf(w, (size_t)k * N + n);
    out[n] = rb(s);
}
__device__ float fb_ln(float v, float* sh) {
    __syncthreads(); sh[threadIdx.x] = v; __syncthreads();
    float s = 0.f, q = 0.f;
    for (int i = 0; i < D; i++) s += sh[i];
    s /= D;
    for (int i = 0; i < D; i++) q += (sh[i] - s) * (sh[i] - s);
    return rb(rb(v - rb(s)) / rb(sqrtf(rb(rb(q / D) + 1e-5f))));
}
__global__ void fb_elem(int stage, CB x, CB c, CB b1, CB b2, __nv_bfloat16* out) {
    __shared__ float sh[D];
    const int i = threadIdx.x;
    if (stage == 0) { const float v = bf(c, i); f_a[i] = rb(v / (1.f + expf(-v))); }
    if (stage == 1) f_a[i] = rb(rb(fb_ln(bf(x, i), sh) * rb(1.f + f_mod[D + i])) + f_mod[i]);
    if (stage == 2) {
        f_x2[i] = rb(bf(x, i) + rb(f_mod[2 * D + i] * f_t[i]));
        f_a[i] = fb_ln(rb(rb(fb_ln(f_x2[i], sh) * rb(1.f + f_mod[4 * D + i])) + f_mod[3 * D + i]), sh);
    }
    if (stage == 3)
        for (int j = i; j < FF; j += D) {
            const float u = rb(f_t[j] + bf(b1, j));
            f_a[j] = rb(0.5f * u * (1.f + tanhf(0.7978845608028654f * (u + 0.044715f * u * u * u))));
        }
    if (stage == 4) out[i] = __float2bfloat16_rn(f_x2[i] + rb(f_mod[5 * D + i] * rb(f_t[i] + bf(b2, i))));
}
__global__ void fb_attn(CB k, CB v) {
    __shared__ float p[WIN], red[128];
    const int h = blockIdx.x, t = threadIdx.x;
    const size_t base = ((size_t)(h / 2) * SK + SK - WIN) * 128;
    float m = -INFINITY, l = 0.f, o = 0.f;
    for (int j = t; j < WIN; j += 128) {
        float s = 0.f;
        for (int d = 0; d < 128; d++) s += f_q[h * 128 + d] * bf(k, base + (size_t)j * 128 + d);
        p[j] = rb(rb(s) * 0.08838834764831845f);
        m = fmaxf(m, p[j]);
    }
    red[t] = m; __syncthreads();
    for (int i = 0; i < 128; i++) m = fmaxf(m, red[i]);
    __syncthreads();
    for (int j = t; j < WIN; j += 128) { p[j] = expf(p[j] - m); l += p[j]; }
    red[t] = l; __syncthreads();
    l = 0.f;
    for (int i = 0; i < 128; i++) l += red[i];
    for (int j = 0; j < WIN; j++) o += rb(p[j] / l) * bf(v, base + (size_t)j * 128 + t);
    f_a[h * 128 + t] = rb(o);
}
void fallback(void* const* in, void* out) {
    float *a, *mod, *q, *t;
    cudaGetSymbolAddress((void**)&a, f_a); cudaGetSymbolAddress((void**)&mod, f_mod);
    cudaGetSymbolAddress((void**)&q, f_q); cudaGetSymbolAddress((void**)&t, f_t);
#define ELEM(s) fb_elem<<<1, D>>>(s, (CB)in[0], (CB)in[10], (CB)in[7], (CB)in[9], (__nv_bfloat16*)out)
    ELEM(0); fb_gemv<<<54, 64>>>(a, (CB)in[11], D, 6 * D, mod);
    ELEM(1); fb_gemv<<<64, 64>>>(a, (CB)in[3], D, 4096, q);
    fb_attn<<<32, 128>>>((CB)in[1], (CB)in[2]); fb_gemv<<<9, 64>>>(a, (CB)in[4], 4096, D, t);
    ELEM(2); fb_gemv<<<72, 64>>>(a, (CB)in[6], D, FF, t);
    ELEM(3); fb_gemv<<<9, 64>>>(a, (CB)in[8], FF, D, t);
    ELEM(4);
#undef ELEM
}

}

extern "C" void kernel_launch(void* const* d_in, const int* in_sizes, int n_in, void* d_out, int out_size) {
    (void)in_sizes; (void)n_in; (void)out_size;
    int dev = 0, sms = 0, occ = 0, mclk = 0, bus = 0;
    cudaGetDevice(&dev);
    cudaDeviceGetAttribute(&sms, cudaDevAttrMultiProcessorCount, dev);
    cudaDeviceGetAttribute(&mclk, cudaDevAttrMemoryClockRate, dev);
    cudaDeviceGetAttribute(&bus, cudaDevAttrGlobalMemoryBusWidth, dev);
    cudaFuncSetAttribute(fused_kernel, cudaFuncAttributeMaxDynamicSharedMemorySize, SM_TOTAL);
    cudaOccupancyMaxActiveBlocksPerMultiprocessor(&occ, fused_kernel, NTHREADS, SM_TOTAL);
    void* fn = nullptr;
    cudaDriverEntryPointQueryResult qr;
    cudaGetDriverEntryPoint("cuTensorMapEncodeTiled", &fn, cudaEnableDefault, &qr);
    if (sms * occ < NATT || !fn) { (void)cudaGetLastError(); fallback(d_in, d_out); return; }
    EncodeFn enc = (EncodeFn)fn;

    Params P;
    make_map(enc, &P.m_wq, d_in[3], 4096, D, 32, 192, CU_TENSOR_MAP_SWIZZLE_64B, CU_TENSOR_MAP_L2_PROMOTION_L2_128B);
    make_map(enc, &P.m_k, d_in[1], 64, (uint64_t)HKV * SK * 2, 64, 128, CU_TENSOR_MAP_SWIZZLE_128B, CU_TENSOR_MAP_L2_PROMOTION_L2_256B);
    make_map(enc, &P.m_v, d_in[2], 64, (uint64_t)HKV * SK * 2, 64, 128, CU_TENSOR_MAP_SWIZZLE_128B, CU_TENSOR_MAP_L2_PROMOTION_L2_256B);
    make_map(enc, &P.m_wo, d_in[4], 64, 4096 * 9, 64, 144, CU_TENSOR_MAP_SWIZZLE_128B, CU_TENSOR_MAP_L2_PROMOTION_L2_256B);
    make_map(enc, &P.m_w1, d_in[6], FF, D, 32, 192, CU_TENSOR_MAP_SWIZZLE_64B, CU_TENSOR_MAP_L2_PROMOTION_L2_128B);
    make_map(enc, &P.m_w1x, d_in[6], FF, D, 16, 192, CU_TENSOR_MAP_SWIZZLE_NONE, CU_TENSOR_MAP_L2_PROMOTION_L2_64B);
    make_map(enc, &P.m_w2, d_in[8], 64, FF * 9, 64, 144, CU_TENSOR_MAP_SWIZZLE_128B, CU_TENSOR_MAP_L2_PROMOTION_L2_256B);
    P.b2 = (const __nv_bfloat16*)d_in[9];
    const double speed = mclk > 0 && bus > 0 ? (double)mclk * bus / (2619000.0 * 5120.0) : 1.0;
    make_schedule(P, speed);
    void* boxp = nullptr;
    cudaGetSymbolAddress(&boxp, g_box);
    uint4* box = (uint4*)(((uintptr_t)boxp + (2 << 20) - 1) & ~(uintptr_t)((2 << 20) - 1));
    fused_kernel<<<NATT, NTHREADS, SM_TOTAL>>>((const __nv_bfloat16*)d_in[11], (const __nv_bfloat16*)d_in[10], (const __nv_bfloat16*)d_in[0],
                                               box, (const __nv_bfloat16*)d_in[7], (__nv_bfloat16*)d_out, P);
}
```
